```python
import torch

def _softmax(x, axis=-1):
    return torch.softmax(x, dim=axis)
def _gelu(x):
    return torch.nn.functional.gelu(x, approximate="tanh")
def _silu(x):
    return torch.nn.functional.silu(x)
def _sigmoid(x):
    return torch.sigmoid(x)
def _layernorm(x, axis=-1, eps=1e-5):
    m = x.mean(dim=axis, keepdim=True)
    v = x.var(dim=axis, keepdim=True, unbiased=False)
    return (x - m) / torch.sqrt(v + eps)
def _scatter_add(tgt, idx, src, axis=0):
    return tgt.clone().index_add_(axis, idx, src)
def _segment_sum(src, seg, n):
    out = torch.zeros((n,) + src.shape[1:], dtype=src.dtype)
    return out.index_add_(0, seg, src)
def _pad(x, pw):
    flat = tuple(v for pair in reversed(pw) for v in pair)
    return torch.nn.functional.pad(x, flat)

kernel_name = 'concat_heads__ssm_conv_s4d__linear_attn_block__prompt'

def setup_inputs():

    _w = (lambda a: (lambda t: t.to(torch.bfloat16) if t.is_floating_point() else t)(torch.as_tensor(a)))
    def _A_setup():
        Bsz, L, D, N = 1, 2048, 640, 128
        return {
            "u": _w((lambda *s: torch.randn(*s, dtype=torch.bfloat16) * 0.05)(Bsz, L, D)),
            "log_A_real": _w((lambda *s: torch.randn(*s, dtype=torch.bfloat16) * 3.2)(D, N) * 0.5),
            "A_imag": _w((lambda *s: torch.randn(*s, dtype=torch.bfloat16) * 0.05)(D, N) * 3.14),
            "C_real": _w((lambda *s: torch.randn(*s, dtype=torch.bfloat16) * 0.2)(D, N) / N ** 0.5),
            "C_imag": _w((lambda *s: torch.randn(*s, dtype=torch.bfloat16) * 0.2)(D, N) / N ** 0.5),
            "log_dt": _w((lambda *s: torch.randn(*s, dtype=torch.bfloat16) * 0.05)(D) * 0.5 - 4.0),
            "D_skip": _w((lambda *s: torch.randn(*s, dtype=torch.bfloat16) * 0.05)(D)),
        }
    _A_in = _A_setup()

    def _B_setup():
        B, S, D = 1, 2048, 640
        return {
            "x": _w((lambda *s: torch.randn(*s, dtype=torch.bfloat16) * 0.05)(B, S, D)),
            "wqkv": _w((lambda *s: torch.randn(*s, dtype=torch.bfloat16) * 0.4)(D, 3 * D)),
            "wo": _w((lambda *s: torch.randn(*s, dtype=torch.bfloat16) * 0.05)(D, D)),
        }
    _B_in = _B_setup()

    return {
        "A_u": _A_in["u"],
        "A_log_A_real": _A_in["log_A_real"],
        "A_A_imag": _A_in["A_imag"],
        "A_C_real": _A_in["C_real"],
        "A_C_imag": _A_in["C_imag"],
        "A_log_dt": _A_in["log_dt"],
        "A_D_skip": _A_in["D_skip"],
        "B_x": _B_in["x"],
        "B_wqkv": _B_in["wqkv"],
        "B_wo": _B_in["wo"],
    }

def reference(A_u, A_log_A_real, A_A_imag, A_C_real, A_C_imag, A_log_dt, A_D_skip, B_x, B_wqkv, B_wo):
    def _A_ref(u, log_A_real, A_imag, C_real, C_imag, log_dt, D_skip):
        L = u.shape[1]
        dt = torch.exp(log_dt)
        A = -torch.exp(log_A_real) + 1j * A_imag
        C = (C_real + 1j * C_imag) * dt[:, None]
        pos = (lambda x, dt: x.to(dt))(torch.arange(L), log_dt.dtype)
        P = torch.exp((A * dt[:, None])[:, :, None] * pos[None, None, :])
        K = 2.0 * torch.einsum("dn,dnl->dl", C, P).real
        L2 = 2 * L
        u_t = (lambda x, *d: x.permute(*d))(u, 0, 2, 1)
        Kf = (lambda x, *a, **k: torch.fft.rfft(x.float(), *a, **k))(K, L2)
        Uf = (lambda x, *a, **k: torch.fft.rfft(x.float(), *a, **k))(u_t, L2)
        y = (lambda x, *a, **k: torch.fft.irfft(x, *a, **k).to(torch.bfloat16))(Uf * Kf[None, :, :], L2)[:, :, :L]
        y = (lambda x, *d: x.permute(*d))(y, 0, 2, 1)
        return y + u * D_skip[None, None, :]

    def _B_ref(x, wqkv, wo):
        B, S, D = x.shape
        H = 32; Dh = D // H
        qkv = (lambda x, *d: x.permute(*d))((x @ wqkv).reshape(B, S, 3, H, Dh), 2, 0, 3, 1, 4)
        q, k, v = qkv[0], qkv[1], qkv[2]
        phi = lambda t: torch.where(t > 0, t + 1, torch.exp(t)) + 1e-6
        pq, pk = phi(q), phi(k)
        kv = torch.einsum("bhsd,bhse->bhde", pk, v)
        z = torch.einsum("bhsd->bhd", pk)
        num = torch.einsum("bhqd,bhde->bhqe", pq, kv)
        den = torch.einsum("bhqd,bhd->bhq", pq, z)[..., None] + 1e-6
        o = num / den
        return (lambda x, *d: x.permute(*d))(o, 0, 2, 1, 3).reshape(B, S, D) @ wo

    a = _A_ref(A_u, A_log_A_real, A_A_imag, A_C_real, A_C_imag, A_log_dt, A_D_skip)
    b = _B_ref(B_x, B_wqkv, B_wo)
    return torch.concatenate([a, b], axis=-1)
```

```cpp
#include <cuda_runtime.h>
#include <cuda.h>
#include <cuda_bf16.h>
#include <cuda_fp16.h>
#include <stdint.h>

namespace {

__device__ __align__(128) uint4    g_uT[640 * 2 * 128];
__device__ __align__(128) uint32_t g_yX[8 * 16 * 80 * 64];
__device__ __align__(128) uint4    g_oX[16 * 40 * 8 * 32];
__device__ __align__(128) float    g_kv[8 * 80 * 22];
__device__ __align__(128) uint32_t g_ctrJ[8 * 32];
__device__ __align__(128) uint32_t g_ctrI[16 * 32];
#define TSTAMP(slot) do { } while (0)

struct Params {
    CUtensorMap mx, mw64, mw16, mu, mout;
    const __nv_bfloat16 *u, *logA, *Aim, *Cre, *Cim, *logdt, *dskip, *wo;
    __nv_bfloat16* out;
    int use_smid;
};

constexpr int STAGE_B = 47104;
constexpr int OFF_UT  = 3 * STAGE_B;
constexpr int UT_CH   = 4352;
constexpr int OFF_PT  = OFF_UT + 5 * UT_CH;
constexpr int PT_CH   = 10304;
constexpr int OFF_KB  = OFF_PT + 5 * PT_CH;
constexpr int KB_WG   = 1296;
constexpr int OFF_BAR = OFF_KB + 2 * KB_WG;
constexpr int SMEM_TOTAL = OFF_BAR + 128;
constexpr int OFF_PK  = 0;
constexpr int OFF_V   = 20480;
constexpr int WO_NB   = 10256;
constexpr int OFF_KVB = 104448;
constexpr int OFF_KVS = 119808;
constexpr int OFF_OUTS = 120832;

__device__ __forceinline__ uint32_t smem_u32(const void* p) { return (uint32_t)__cvta_generic_to_shared(p); }
__device__ __forceinline__ void mbar_init(uint32_t bar, uint32_t cnt) { asm volatile("mbarrier.init.shared::cta.b64 [%0], %1;" :: "r"(bar), "r"(cnt) : "memory"); }
__device__ __forceinline__ void mbar_expect_tx(uint32_t bar, uint32_t bytes) { asm volatile("mbarrier.arrive.expect_tx.shared::cta.b64 _, [%0], %1;" :: "r"(bar), "r"(bytes) : "memory"); }
__device__ __forceinline__ void mbar_arrive(uint32_t bar) { asm volatile("mbarrier.arrive.shared::cta.b64 _, [%0];" :: "r"(bar) : "memory"); }
__device__ __forceinline__ void mbar_wait(uint32_t bar, uint32_t parity) {
    uint32_t done; int it = 0;
    do {
        asm volatile("{ .reg .pred p; mbarrier.try_wait.parity.shared::cta.b64 p, [%1], %2; selp.u32 %0, 1, 0, p; }" : "=r"(done) : "r"(bar), "r"(parity) : "memory");
        if (++it > (1 << 22)) __trap();
    } while (!done);
}
__device__ __forceinline__ void bar_sync(int id, int n) { asm volatile("bar.sync %0, %1;" :: "r"(id), "r"(n) : "memory"); }
__device__ __forceinline__ void fence_async() { asm volatile("fence.proxy.async;" ::: "memory"); }
__device__ __forceinline__ void fence_async_smem() { asm volatile("fence.proxy.async.shared::cta;" ::: "memory"); }
__device__ __forceinline__ void tma2d(uint32_t dst, const CUtensorMap* m, uint32_t bar, int c0, int c1) {
    asm volatile("cp.async.bulk.tensor.2d.shared::cluster.global.mbarrier::complete_tx::bytes [%0], [%1, {%3, %4}], [%2];" :: "r"(dst), "l"(m), "r"(bar), "r"(c0), "r"(c1) : "memory");
}
__device__ __forceinline__ void tma3d(uint32_t dst, const CUtensorMap* m, uint32_t bar, int c0, int c1, int c2) {
    asm volatile("cp.async.bulk.tensor.3d.shared::cluster.global.mbarrier::complete_tx::bytes [%0], [%1, {%3, %4, %5}], [%2];" :: "r"(dst), "l"(m), "r"(bar), "r"(c0), "r"(c1), "r"(c2) : "memory");
}
__device__ __forceinline__ void bulk_g2s(uint32_t dst, const void* src, uint32_t bytes, uint32_t bar) {
    asm volatile("cp.async.bulk.shared::cluster.global.mbarrier::complete_tx::bytes [%0], [%1], %2, [%3];" :: "r"(dst), "l"(src), "r"(bytes), "r"(bar) : "memory");
}
__device__ __forceinline__ void wg_fence() { asm volatile("wgmma.fence.sync.aligned;" ::: "memory"); }
__device__ __forceinline__ void wg_commit() { asm volatile("wgmma.commit_group.sync.aligned;" ::: "memory"); }
template <int N> __device__ __forceinline__ void wg_wait() { asm volatile("wgmma.wait_group.sync.aligned %0;" :: "n"(N) : "memory"); }
__device__ __forceinline__ uint32_t desc_lo(uint32_t addr, uint32_t lbo) { return __shfl_sync(0xffffffffu, ((addr & 0x3FFFF) >> 4) | ((lbo >> 4) << 16), 0); }
__host__ __device__ constexpr uint32_t desc_hi(uint32_t sbo, uint32_t sw) { return (sbo >> 4) | (sw << 30); }
template <int I> struct IC { static constexpr int v = I; };
template <int B, int E, class F> __device__ __forceinline__ void sfor(F&& f) { if constexpr (B < E) { f(IC<B>{}); sfor<B + 1, E>(f); } }
__device__ __forceinline__ void ldsm4t(uint32_t& r0, uint32_t& r1, uint32_t& r2, uint32_t& r3, uint32_t addr) {
    asm volatile("ldmatrix.sync.aligned.m8n8.x4.trans.shared.b16 {%0,%1,%2,%3}, [%4];" : "=r"(r0), "=r"(r1), "=r"(r2), "=r"(r3) : "r"(addr) : "memory");
}
__device__ __forceinline__ void stsm4(uint32_t addr, uint32_t r0, uint32_t r1, uint32_t r2, uint32_t r3) {
    asm volatile("stmatrix.sync.aligned.m8n8.x4.shared.b16 [%0], {%1,%2,%3,%4};" :: "r"(addr), "r"(r0), "r"(r1), "r"(r2), "r"(r3) : "memory");
}
__device__ __forceinline__ uint32_t lds32(uint32_t a) { uint32_t v; asm volatile("ld.shared.b32 %0, [%1];" : "=r"(v) : "r"(a) : "memory"); return v; }
__device__ __forceinline__ uint32_t pack_bf16(float lo, float hi) { uint32_t r; asm("cvt.rn.bf16x2.f32 %0, %1, %2;" : "=r"(r) : "f"(hi), "f"(lo)); return r; }
__device__ __forceinline__ uint32_t pack_f16(float lo, float hi) { uint32_t r; asm("cvt.rn.f16x2.f32 %0, %1, %2;" : "=r"(r) : "f"(hi), "f"(lo)); return r; }
__device__ __forceinline__ float bf_lo(uint32_t v) { return __uint_as_float(v << 16); }
__device__ __forceinline__ float bf_hi(uint32_t v) { return __uint_as_float(v & 0xFFFF0000u); }
__device__ __forceinline__ float bf16r(float x) { return __bfloat162float(__float2bfloat16_rn(x)); }
__device__ __forceinline__ float ex2f(float x) { float r; asm("ex2.approx.ftz.f32 %0, %1;" : "=f"(r) : "f"(x)); return r; }
__device__ __forceinline__ uint32_t hadd2_bf(uint32_t a, uint32_t b) { uint32_t r; asm("add.rn.bf16x2 %0, %1, %2;" : "=r"(r) : "r"(a), "r"(b)); return r; }
__device__ __forceinline__ uint32_t hmul2_bf(uint32_t a, uint32_t b) { uint32_t r; asm("mul.rn.bf16x2 %0, %1, %2;" : "=r"(r) : "r"(a), "r"(b)); return r; }
__device__ __forceinline__ uint4 ldcg4(const uint4* p) { uint4 v; asm volatile("ld.global.cg.v4.u32 {%0,%1,%2,%3}, [%4];" : "=r"(v.x), "=r"(v.y), "=r"(v.z), "=r"(v.w) : "l"(p) : "memory"); return v; }

__device__ __forceinline__ uint32_t phi2(float a, float b) {
    uint32_t t = pack_bf16(a, b);
    uint32_t p = hadd2_bf(t, 0x3F803F80u);
    uint32_t e = pack_bf16(ex2f(bf_lo(t) * 1.4426950408889634f), ex2f(bf_hi(t) * 1.4426950408889634f));
    uint32_t m; asm("set.gt.u32.bf16x2 %0, %1, %2;" : "=r"(m) : "r"(t), "r"(0u));
    return hadd2_bf((p & m) | (e & ~m), 0x35863586u);
}

template <uint32_t PERIOD> __device__ __forceinline__ uint32_t ctr_arrive(uint32_t* c, uint32_t inc = 1) {
    __threadfence();
    uint32_t old = atomicAdd(c, inc);
    return (old & ~(PERIOD - 1)) + PERIOD;
}
__device__ __forceinline__ void ctr_wait(const uint32_t* c, uint32_t target) {
    uint32_t v; int it = 0;
    do {
        asm volatile("ld.acquire.gpu.global.u32 %0, [%1];" : "=r"(v) : "l"(c) : "memory");
        if (++it > (1 << 22)) __trap();
    } while ((int)(v - target) < 0);
}

template <int TB, uint32_t BHI, int BOFF> __device__ __forceinline__ void wgmma_rs_n32(float (&d)[16], uint32_t a0, uint32_t a1, uint32_t a2, uint32_t a3, uint32_t blo, int sd) {
    asm volatile("{ .reg .pred p; .reg .b32 lb; .reg .b64 db; setp.ne.b32 p, %21, 0; add.u32 lb, %20, %24; mov.b64 db, {lb, %23};\n"
        "wgmma.mma_async.sync.aligned.m64n32k16.f32.bf16.bf16 {%0, %1, %2, %3, %4, %5, %6, %7, %8, %9, %10, %11, %12, %13, %14, %15}, {%16, %17, %18, %19}, db, p, 1, 1, %22; }\n"
        : "+f"(d[0]), "+f"(d[1]), "+f"(d[2]), "+f"(d[3]), "+f"(d[4]), "+f"(d[5]), "+f"(d[6]), "+f"(d[7]), "+f"(d[8]), "+f"(d[9]), "+f"(d[10]), "+f"(d[11]), "+f"(d[12]), "+f"(d[13]), "+f"(d[14]), "+f"(d[15])
        : "r"(a0), "r"(a1), "r"(a2), "r"(a3), "r"(blo), "r"(sd), "n"(TB), "n"(BHI), "n"(BOFF));
}
template <int TB, uint32_t BHI, int BOFF> __device__ __forceinline__ void wgmma_rs_n80(float (&d)[40], uint32_t a0, uint32_t a1, uint32_t a2, uint32_t a3, uint32_t blo, int sd) {
    asm volatile("{ .reg .pred p; .reg .b32 lb; .reg .b64 db; setp.ne.b32 p, %45, 0; add.u32 lb, %44, %48; mov.b64 db, {lb, %47};\n"
        "wgmma.mma_async.sync.aligned.m64n80k16.f32.bf16.bf16 {%0, %1, %2, %3, %4, %5, %6, %7, %8, %9, %10, %11, %12, %13, %14, %15, %16, %17, %18, %19, %20, %21, %22, %23, %24, %25, %26, %27, %28, %29, %30, %31, %32, %33, %34, %35, %36, %37, %38, %39}, {%40, %41, %42, %43}, db, p, 1, 1, %46; }\n"
        : "+f"(d[0]), "+f"(d[1]), "+f"(d[2]), "+f"(d[3]), "+f"(d[4]), "+f"(d[5]), "+f"(d[6]), "+f"(d[7]), "+f"(d[8]), "+f"(d[9]), "+f"(d[10]), "+f"(d[11]), "+f"(d[12]), "+f"(d[13]), "+f"(d[14]), "+f"(d[15]), "+f"(d[16]), "+f"(d[17]), "+f"(d[18]), "+f"(d[19]), "+f"(d[20]), "+f"(d[21]), "+f"(d[22]), "+f"(d[23]), "+f"(d[24]), "+f"(d[25]), "+f"(d[26]), "+f"(d[27]), "+f"(d[28]), "+f"(d[29]), "+f"(d[30]), "+f"(d[31]), "+f"(d[32]), "+f"(d[33]), "+f"(d[34]), "+f"(d[35]), "+f"(d[36]), "+f"(d[37]), "+f"(d[38]), "+f"(d[39])
        : "r"(a0), "r"(a1), "r"(a2), "r"(a3), "r"(blo), "r"(sd), "n"(TB), "n"(BHI), "n"(BOFF));
}
template <int TB, uint32_t BHI, int BOFF> __device__ __forceinline__ void wgmma_rs_n96(float (&d)[48], uint32_t a0, uint32_t a1, uint32_t a2, uint32_t a3, uint32_t blo, int sd) {
    asm volatile("{ .reg .pred p; .reg .b32 lb; .reg .b64 db; setp.ne.b32 p, %53, 0; add.u32 lb, %52, %56; mov.b64 db, {lb, %55};\n"
        "wgmma.mma_async.sync.aligned.m64n96k16.f32.bf16.bf16 {%0, %1, %2, %3, %4, %5, %6, %7, %8, %9, %10, %11, %12, %13, %14, %15, %16, %17, %18, %19, %20, %21, %22, %23, %24, %25, %26, %27, %28, %29, %30, %31, %32, %33, %34, %35, %36, %37, %38, %39, %40, %41, %42, %43, %44, %45, %46, %47}, {%48, %49, %50, %51}, db, p, 1, 1, %54; }\n"
        : "+f"(d[0]), "+f"(d[1]), "+f"(d[2]), "+f"(d[3]), "+f"(d[4]), "+f"(d[5]), "+f"(d[6]), "+f"(d[7]), "+f"(d[8]), "+f"(d[9]), "+f"(d[10]), "+f"(d[11]), "+f"(d[12]), "+f"(d[13]), "+f"(d[14]), "+f"(d[15]), "+f"(d[16]), "+f"(d[17]), "+f"(d[18]), "+f"(d[19]), "+f"(d[20]), "+f"(d[21]), "+f"(d[22]), "+f"(d[23]), "+f"(d[24]), "+f"(d[25]), "+f"(d[26]), "+f"(d[27]), "+f"(d[28]), "+f"(d[29]), "+f"(d[30]), "+f"(d[31]), "+f"(d[32]), "+f"(d[33]), "+f"(d[34]), "+f"(d[35]), "+f"(d[36]), "+f"(d[37]), "+f"(d[38]), "+f"(d[39]), "+f"(d[40]), "+f"(d[41]), "+f"(d[42]), "+f"(d[43]), "+f"(d[44]), "+f"(d[45]), "+f"(d[46]), "+f"(d[47])
        : "r"(a0), "r"(a1), "r"(a2), "r"(a3), "r"(blo), "r"(sd), "n"(TB), "n"(BHI), "n"(BOFF));
}
template <int TA, int TB, uint32_t AHI, int AOFF, uint32_t BHI, int BOFF> __device__ __forceinline__ void wgmma_ss_n48(float (&d)[24], uint32_t alo, uint32_t blo, int sd) {
    asm volatile("{ .reg .pred p; .reg .b32 la, lb; .reg .b64 da, db; setp.ne.b32 p, %26, 0; add.u32 la, %24, %30; mov.b64 da, {la, %29}; add.u32 lb, %25, %32; mov.b64 db, {lb, %31};\n"
        "wgmma.mma_async.sync.aligned.m64n48k16.f32.bf16.bf16 {%0, %1, %2, %3, %4, %5, %6, %7, %8, %9, %10, %11, %12, %13, %14, %15, %16, %17, %18, %19, %20, %21, %22, %23}, da, db, p, 1, 1, %27, %28; }\n"
        : "+f"(d[0]), "+f"(d[1]), "+f"(d[2]), "+f"(d[3]), "+f"(d[4]), "+f"(d[5]), "+f"(d[6]), "+f"(d[7]), "+f"(d[8]), "+f"(d[9]), "+f"(d[10]), "+f"(d[11]), "+f"(d[12]), "+f"(d[13]), "+f"(d[14]), "+f"(d[15]), "+f"(d[16]), "+f"(d[17]), "+f"(d[18]), "+f"(d[19]), "+f"(d[20]), "+f"(d[21]), "+f"(d[22]), "+f"(d[23])
        : "r"(alo), "r"(blo), "r"(sd), "n"(TA), "n"(TB), "n"(AHI), "n"(AOFF), "n"(BHI), "n"(BOFF));
}
template <int TA, int TB, uint32_t AHI, int AOFF, uint32_t BHI, int BOFF> __device__ __forceinline__ void wgmma_ss_n192(float (&d)[96], uint32_t alo, uint32_t blo, int sd) {
    asm volatile("{ .reg .pred p; .reg .b32 la, lb; .reg .b64 da, db; setp.ne.b32 p, %98, 0; add.u32 la, %96, %102; mov.b64 da, {la, %101}; add.u32 lb, %97, %104; mov.b64 db, {lb, %103};\n"
        "wgmma.mma_async.sync.aligned.m64n192k16.f32.bf16.bf16 {%0, %1, %2, %3, %4, %5, %6, %7, %8, %9, %10, %11, %12, %13, %14, %15, %16, %17, %18, %19, %20, %21, %22, %23, %24, %25, %26, %27, %28, %29, %30, %31, %32, %33, %34, %35, %36, %37, %38, %39, %40, %41, %42, %43, %44, %45, %46, %47, %48, %49, %50, %51, %52, %53, %54, %55, %56, %57, %58, %59, %60, %61, %62, %63, %64, %65, %66, %67, %68, %69, %70, %71, %72, %73, %74, %75, %76, %77, %78, %79, %80, %81, %82, %83, %84, %85, %86, %87, %88, %89, %90, %91, %92, %93, %94, %95}, da, db, p, 1, 1, %99, %100; }\n"
        : "+f"(d[0]), "+f"(d[1]), "+f"(d[2]), "+f"(d[3]), "+f"(d[4]), "+f"(d[5]), "+f"(d[6]), "+f"(d[7]), "+f"(d[8]), "+f"(d[9]), "+f"(d[10]), "+f"(d[11]), "+f"(d[12]), "+f"(d[13]), "+f"(d[14]), "+f"(d[15]), "+f"(d[16]), "+f"(d[17]), "+f"(d[18]), "+f"(d[19]), "+f"(d[20]), "+f"(d[21]), "+f"(d[22]), "+f"(d[23]), "+f"(d[24]), "+f"(d[25]), "+f"(d[26]), "+f"(d[27]), "+f"(d[28]), "+f"(d[29]), "+f"(d[30]), "+f"(d[31]), "+f"(d[32]), "+f"(d[33]), "+f"(d[34]), "+f"(d[35]), "+f"(d[36]), "+f"(d[37]), "+f"(d[38]), "+f"(d[39]), "+f"(d[40]), "+f"(d[41]), "+f"(d[42]), "+f"(d[43]), "+f"(d[44]), "+f"(d[45]), "+f"(d[46]), "+f"(d[47]), "+f"(d[48]), "+f"(d[49]), "+f"(d[50]), "+f"(d[51]), "+f"(d[52]), "+f"(d[53]), "+f"(d[54]), "+f"(d[55]), "+f"(d[56]), "+f"(d[57]), "+f"(d[58]), "+f"(d[59]), "+f"(d[60]), "+f"(d[61]), "+f"(d[62]), "+f"(d[63]), "+f"(d[64]), "+f"(d[65]), "+f"(d[66]), "+f"(d[67]), "+f"(d[68]), "+f"(d[69]), "+f"(d[70]), "+f"(d[71]), "+f"(d[72]), "+f"(d[73]), "+f"(d[74]), "+f"(d[75]), "+f"(d[76]), "+f"(d[77]), "+f"(d[78]), "+f"(d[79]), "+f"(d[80]), "+f"(d[81]), "+f"(d[82]), "+f"(d[83]), "+f"(d[84]), "+f"(d[85]), "+f"(d[86]), "+f"(d[87]), "+f"(d[88]), "+f"(d[89]), "+f"(d[90]), "+f"(d[91]), "+f"(d[92]), "+f"(d[93]), "+f"(d[94]), "+f"(d[95])
        : "r"(alo), "r"(blo), "r"(sd), "n"(TA), "n"(TB), "n"(AHI), "n"(AOFF), "n"(BHI), "n"(BOFF));
}

struct cpx { float r, i; };
__device__ __forceinline__ cpx cmul(cpx a, cpx b) { return { a.r * b.r - a.i * b.i, a.r * b.i + a.i * b.r }; }
__device__ __forceinline__ cpx csq(cpx a) { return { a.r * a.r - a.i * a.i, (a.r + a.r) * a.i }; }
__device__ __forceinline__ void mma_f16(float (&d)[4], uint32_t a0, uint32_t a1, uint32_t a2, uint32_t a3, uint32_t b0, uint32_t b1) {
    asm volatile("mma.sync.aligned.m16n8k16.row.col.f32.f16.f16.f32 {%0,%1,%2,%3}, {%4,%5,%6,%7}, {%8,%9}, {%0,%1,%2,%3};"
        : "+f"(d[0]), "+f"(d[1]), "+f"(d[2]), "+f"(d[3]) : "r"(a0), "r"(a1), "r"(a2), "r"(a3), "r"(b0), "r"(b1));
}

__device__ __forceinline__ void issue_stage(const Params& P, uint32_t sb, uint32_t fullbar, int s, int kb, int ti, int tj) {
    uint32_t st = sb + s * STAGE_B;
    mbar_expect_tx(fullbar, STAGE_B);
    tma2d(st, &P.mx, fullbar, kb * 64, ti * 128);
    tma3d(st + 16384, &P.mw64, fullbar, tj * 80, kb * 64, 0);
    tma3d(st + 40960, &P.mw16, fullbar, tj * 80 + 64, kb * 64, 0);
}

__global__ void __launch_bounds__(512, 1) fused_kernel(const __grid_constant__ Params P) {
    extern __shared__ __align__(1024) unsigned char smem[];
    const uint32_t sb = smem_u32(smem);
    const int tid = threadIdx.x, lane = tid & 31;
    const int warp = __shfl_sync(0xffffffffu, tid >> 5, 0), wg = warp >> 2;
    const int g = lane >> 2, t = lane & 3;
    int ti, tj;
    if (P.use_smid) {
        uint32_t s; asm volatile("mov.u32 %0, %%smid;" : "=r"(s));
        int gp, rd;
        if (s < 64) { gp = (s >> 1) & 7; rd = s >> 4; }
        else if (s < 120) { int q = (s - 64) >> 1; gp = 1 + q % 7; rd = 4 + q / 7; }
        else if (s < 124) { gp = -1; rd = 0; }
        else { gp = 0; rd = 4 + ((s - 124) >> 1); }
        if (gp < 0) {
            if (tid < 16) { uint32_t tg = ctr_arrive<16>(&g_ctrI[tid * 32], 2); ctr_wait(&g_ctrI[tid * 32], tg); }
            return;
        }
        ti = 2 * gp + (s & 1); tj = rd;
    } else { ti = blockIdx.x & 15; tj = blockIdx.x >> 4; }
    const uint32_t bFull = sb + OFF_BAR, bU = bFull + 24, bUT = bFull + 32, bY = bFull + 40, bSu = bFull + 48;
    uint32_t* relcnt = (uint32_t*)(smem + OFF_BAR + 64);
    if (tid == 0) {
        for (int s = 0; s < 3; s++) { mbar_init(bFull + 8 * s, 1); relcnt[s] = 0; }
        mbar_init(bU, 1); mbar_init(bUT, 1); mbar_init(bY, 1); mbar_init(bSu, 1);
        asm volatile("fence.mbarrier_init.release.cluster;" ::: "memory");
        fence_async_smem();
        issue_stage(P, sb, bFull, 0, 0, ti, tj);
        mbar_expect_tx(bU, 128 * 160);
        tma2d(sb + OFF_UT, &P.mu, bU, tj * 80, ti * 128);
        issue_stage(P, sb, bFull + 8, 1, 1, ti, tj);
        issue_stage(P, sb, bFull + 16, 2, 2, ti, tj);
        if (P.use_smid) atomicAdd(&g_ctrI[ti * 32], 1);
        asm volatile("cp.async.bulk.prefetch.L2.global [%0], %1;" :: "l"(P.wo + (ti * 8 + tj) * 3200), "r"(6400) : "memory");
    }
    __syncthreads();

    if (wg < 2) {
        asm volatile("setmaxnreg.inc.sync.aligned.u32 152;");
        const int wq = warp & 3;
        uint32_t pq[20];
        {
            float acc1[96], acc2[24];
            #pragma unroll 1
            for (int kb = 0; kb < 10; kb++) {
                const int s = kb % 3;
                mbar_wait(bFull + 8 * s, (kb / 3) & 1);
                const uint32_t st = sb + s * STAGE_B;
                const uint32_t da = desc_lo(st + wg * 8192, 16), db = desc_lo(st + 16384, 8192), dc = desc_lo(st + 40960, 2048);
                wg_fence();
                sfor<0, 4>([&](auto K) { constexpr int ks = K.v;
                    wgmma_ss_n192<0, 1, desc_hi(1024, 1), 2 * ks, desc_hi(1024, 1), 128 * ks>(acc1, da, db, (kb | ks) != 0);
                    wgmma_ss_n48<0, 1, desc_hi(1024, 1), 2 * ks, desc_hi(256, 3), 32 * ks>(acc2, da, dc, (kb | ks) != 0);
                });
                wg_commit();
                if (kb > 0 && kb < 8) {
                    wg_wait<1>();
                    if (lane == 0) {
                        const int sp = (kb - 1) % 3;
                        if ((atomicAdd(&relcnt[sp], 1) & 7) == 7) issue_stage(P, sb, bFull + 8 * sp, sp, kb + 2, ti, tj);
                    }
                    __syncwarp();
                }
            }
            wg_wait<0>();
            if (tid == 0) TSTAMP(0);
            uint32_t pk[20], vv[20];
            #pragma unroll
            for (int c = 0; c < 10; c++) {
                const float* K = c < 8 ? &acc1[4 * (8 + c)] : &acc2[4 * (2 + c - 8)];
                const float* V = c < 8 ? &acc1[4 * (16 + c)] : &acc2[4 * (4 + c - 8)];
                pk[2 * c] = phi2(K[0], K[1]); pk[2 * c + 1] = phi2(K[2], K[3]);
                vv[2 * c] = pack_bf16(V[0], V[1]); vv[2 * c + 1] = pack_bf16(V[2], V[3]);
            }
            bar_sync(1, 256);
            {
                const uint32_t rowoff = (uint32_t)(wg * 64 + wq * 16 + ((lane >> 3) & 1) * 8 + (lane & 7)) * 16;
                const int hi = lane >> 4;
                #pragma unroll
                for (int c = 0; c < 10; c += 2) {
                    stsm4(sb + OFF_PK + (c + hi) * 2048 + rowoff, pk[2 * c], pk[2 * c + 1], pk[2 * c + 2], pk[2 * c + 3]);
                    const int vb = c + hi + ((c + hi) >= 5 ? 1 : 0);
                    stsm4(sb + OFF_V + vb * 2048 + rowoff, vv[2 * c], vv[2 * c + 1], vv[2 * c + 2], vv[2 * c + 3]);
                }
                if (tid < 128) *(uint4*)(smem + OFF_V + 5 * 2048 + tid * 16) = make_uint4(0x3F803F80u, 0x3F803F80u, 0x3F803F80u, 0x3F803F80u);
                for (int i = tid; i < 960; i += 256) *(uint4*)(smem + OFF_KVB + i * 16) = make_uint4(0, 0, 0, 0);
            }
            asm volatile("setmaxnreg.dec.sync.aligned.u32 136;");
            fence_async_smem();
            bar_sync(1, 256);
            {
                float kv[24];
                const uint32_t da = desc_lo(sb + OFF_PK + wg * 5 * 2048, 128), db = desc_lo(sb + OFF_V + wg * 5 * 2048, 128);
                wg_fence();
                sfor<0, 8>([&](auto K) { constexpr int ks = K.v; wgmma_ss_n48<1, 1, desc_hi(2048, 0), 16 * ks, desc_hi(2048, 0), 16 * ks>(kv, da, db, ks != 0); });
                wg_commit();
                wg_wait<0>();
                float* S = (float*)(smem + OFF_KVS);
                #pragma unroll
                for (int h = 0; h < 2; h++) {
                    const int d = wq * 16 + g + 8 * h;
                    if (d < 40) {
                        const int lo = d < 20 ? 0 : 20;
                        float* row = S + (wg * 40 + d) * 22;
                        #pragma unroll
                        for (int tau = 0; tau < 6; tau++) {
                            const int blk = tau - wg;
                            const float2 val = make_float2(kv[4 * tau + 2 * h], kv[4 * tau + 2 * h + 1]);
                            if (blk < 0 || blk > 4) { if (t == 0) *(float2*)(row + 20) = val; }
                            else { const int e = blk * 8 + 2 * t - lo; if (e >= 0 && e < 20) *(float2*)(row + e) = val; }
                        }
                    }
                }
            }
            fence_async_smem();
            bar_sync(1, 256);
            uint32_t kv_target = 0;
            if (tid == 0) {
                TSTAMP(1);
                mbar_wait(bSu, 0);
                fence_async();
                asm volatile("cp.reduce.async.bulk.global.shared::cta.bulk_group.add.f32 [%0], [%1], %2;" :: "l"(g_kv + tj * 1760), "r"(sb + OFF_KVS), "r"(7040) : "memory");
                asm volatile("cp.async.bulk.commit_group;" ::: "memory");
                asm volatile("cp.async.bulk.wait_group 0;" ::: "memory");
                kv_target = ctr_arrive<16>(&g_ctrJ[tj * 32 + 1]);
                TSTAMP(2);
            }
            __syncwarp();
            #pragma unroll 5
            for (int it = 0; it < 25; it++) {
                const int id = tid + 256 * it, k = id / 10, nb = id - k * 10;
                asm volatile("cp.async.cg.shared.global [%0], [%1], 16;" :: "r"(sb + nb * WO_NB + k * 16), "l"(P.wo + k * 640 + tj * 80 + nb * 8) : "memory");
            }
            asm volatile("cp.async.commit_group;" ::: "memory");
            #pragma unroll
            for (int c = 0; c < 10; c++) {
                const float* Q = c < 8 ? &acc1[4 * c] : &acc2[4 * (c - 8)];
                pq[2 * c] = phi2(Q[0], Q[1]); pq[2 * c + 1] = phi2(Q[2], Q[3]);
            }
            if (tid == 0) { ctr_wait(&g_ctrJ[tj * 32 + 1], kv_target); TSTAMP(3); }
        }
        bar_sync(1, 256);
        {
            const float2* src = (const float2*)(g_kv + tj * 1760);
            float2 v[4];
            #pragma unroll
            for (int r = 0; r < 4; r++) { const int id = tid + 256 * r; if (id < 880) v[r] = __ldcg(src + id); }
            #pragma unroll
            for (int r = 0; r < 4; r++) {
                const int id = tid + 256 * r;
                if (id < 880) {
                    const int d = id / 11, e2 = id - d * 11, h = d / 20;
                    const uint32_t pw = pack_bf16(v[r].x, v[r].y);
                    if (e2 < 10) { const int n = h * 20 + 2 * e2; *(uint32_t*)(smem + OFF_KVB + (n >> 3) * 1280 + d * 16 + (n & 7) * 2) = pw; }
                    else { const uint32_t z = (h & 1) ? (pw & 0xFFFF0000u) : (pw & 0xFFFFu); *(uint4*)(smem + OFF_KVB + (10 + (h >> 1)) * 1280 + d * 16) = make_uint4(z, z, z, z); }
                }
            }
        }
        fence_async_smem();
        bar_sync(1, 256);
        uint32_t fr[3][20];
        {
            float nd[48];
            const uint32_t db = desc_lo(sb + OFF_KVB, 128);
            wg_fence();
            sfor<0, 5>([&](auto K) { constexpr int ks = K.v; wgmma_rs_n96<1, desc_hi(1280, 0), 16 * ks>(nd, pq[4 * ks], pq[4 * ks + 1], pq[4 * ks + 2], pq[4 * ks + 3], db, ks != 0); });
            wg_commit();
            wg_wait<0>();
            float rc[2][4];
            #pragma unroll
            for (int hd = 0; hd < 4; hd++)
                #pragma unroll
                for (int h = 0; h < 2; h++) rc[h][hd] = __fdividef(1.f, bf16r(bf16r(nd[40 + (hd >> 1) * 4 + 2 * h + (hd & 1)]) + 1e-6f));
            #pragma unroll
            for (int c = 0; c < 10; c++)
                #pragma unroll
                for (int h = 0; h < 2; h++) {
                    float r;
                    if (c == 2) r = t < 2 ? rc[h][0] : rc[h][1];
                    else if (c == 7) r = t < 2 ? rc[h][2] : rc[h][3];
                    else r = rc[h][(c * 8) / 20];
                    const uint32_t nb = pack_bf16(nd[4 * c + 2 * h], nd[4 * c + 2 * h + 1]);
                    fr[2][2 * c + h] = pack_bf16(bf_lo(nb) * r, bf_hi(nb) * r);
                }
        }
        uint4* ox = g_oX + (ti * 40 * 8 + warp) * 32 + lane;
        #pragma unroll
        for (int ks = 0; ks < 5; ks++) ox[(tj * 5 + ks) * 256] = make_uint4(fr[2][4 * ks], fr[2][4 * ks + 1], fr[2][4 * ks + 2], fr[2][4 * ks + 3]);
        bar_sync(5 + wg, 128);
        if ((tid & 127) == 0) {
            if (tid == 0) TSTAMP(4);
            const uint32_t tg = ctr_arrive<8>(&g_ctrI[ti * 32 + 1 + wg]);
            ctr_wait(&g_ctrI[ti * 32 + 1 + wg], tg);
            if (tid == 0) TSTAMP(5);
        }
        asm volatile("cp.async.wait_all;" ::: "memory");
        fence_async_smem();
        bar_sync(1, 256);
        {
            float acc[40];
            const uint32_t db = desc_lo(sb, 128);
            #define LOAD_SLICE(buf, slot) { const int sl = (slot) < tj ? (slot) : (slot) + 1; \
                _Pragma("unroll") for (int ks = 0; ks < 5; ks++) { const uint4 v = ldcg4(ox + (sl * 5 + ks) * 256); \
                    fr[buf][4 * ks] = v.x; fr[buf][4 * ks + 1] = v.y; fr[buf][4 * ks + 2] = v.z; fr[buf][4 * ks + 3] = v.w; } }
            #define MMA_SLICE(buf, sl, first) { const uint32_t dbs = db + (sl) * 80; wg_fence(); \
                sfor<0, 5>([&](auto K) { constexpr int ks = K.v; wgmma_rs_n80<1, desc_hi(WO_NB, 0), 16 * ks>(acc, fr[buf][4 * ks], fr[buf][4 * ks + 1], fr[buf][4 * ks + 2], fr[buf][4 * ks + 3], dbs, !((first) && ks == 0)); }); \
                wg_commit(); }
            #define SL(slot) ((slot) < tj ? (slot) : (slot) + 1)
            LOAD_SLICE(0, 0) LOAD_SLICE(1, 1)
            MMA_SLICE(2, tj, true)
            wg_wait<0>(); LOAD_SLICE(2, 2)
            MMA_SLICE(0, SL(0), false)
            MMA_SLICE(1, SL(1), false)
            wg_wait<1>(); LOAD_SLICE(0, 3)
            MMA_SLICE(2, SL(2), false)
            wg_wait<1>(); LOAD_SLICE(1, 4)
            MMA_SLICE(0, SL(3), false)
            wg_wait<1>(); LOAD_SLICE(2, 5)
            MMA_SLICE(1, SL(4), false)
            wg_wait<1>(); LOAD_SLICE(0, 6)
            MMA_SLICE(2, SL(5), false)
            MMA_SLICE(0, SL(6), false)
            wg_wait<0>();
            if (tid == 0) TSTAMP(6);
            const uint32_t rowa = sb + OFF_OUTS + (uint32_t)(wg * 64 + wq * 16 + ((lane >> 3) & 1) * 8 + (lane & 7)) * 160 + (lane >> 4) * 16;
            #pragma unroll
            for (int c = 0; c < 10; c += 2)
                stsm4(rowa + c * 16, pack_bf16(acc[4 * c], acc[4 * c + 1]), pack_bf16(acc[4 * c + 2], acc[4 * c + 3]),
                      pack_bf16(acc[4 * c + 4], acc[4 * c + 5]), pack_bf16(acc[4 * c + 6], acc[4 * c + 7]));
            fence_async_smem();
            bar_sync(5 + wg, 128);
            if ((tid & 127) == 0) {
                asm volatile("cp.async.bulk.tensor.2d.global.shared::cta.bulk_group [%0, {%2, %3}], [%1];" :: "l"(&P.mout), "r"(sb + OFF_OUTS + wg * 64 * 160), "r"(640 + tj * 80), "r"(ti * 128 + wg * 64) : "memory");
                asm volatile("cp.async.bulk.commit_group;" ::: "memory");
                asm volatile("cp.async.bulk.wait_group.read 0;" ::: "memory");
                if (tid == 0) TSTAMP(7);
            }
        }
    } else {
        asm volatile("setmaxnreg.dec.sync.aligned.u32 104;");
        const int aw = wg - 2, wa = warp - 8, w = warp & 3, tw = tid & 127, ta = tid - 256;
        const int ch0 = tj * 80 + ti * 5;
        const int nch = aw == 0 ? 3 : 2;
        float pl[3][4], pdt[3];
        #pragma unroll
        for (int k = 0; k < 3; k++) {
            const int ch = ch0 + (k < nch ? aw + 2 * k : aw);
            pl[k][0] = __bfloat162float(P.logA[ch * 128 + tw]); pl[k][1] = __bfloat162float(P.Aim[ch * 128 + tw]);
            pl[k][2] = __bfloat162float(P.Cre[ch * 128 + tw]);  pl[k][3] = __bfloat162float(P.Cim[ch * 128 + tw]);
            pdt[k] = __bfloat162float(P.logdt[ch]);
        }
        if (ti == 0) for (int i = ta; i < 440; i += 256) *(float4*)(g_kv + tj * 1760 + i * 4) = make_float4(0.f, 0.f, 0.f, 0.f);
        mbar_wait(bU, 0);
        {
            const int m = lane >> 3, r = lane & 7;
            #pragma unroll
            for (int k = 0; k < 5; k++) {
                const int id = wa * 5 + k, cb = id >> 2, a = id & 1, par = (id >> 1) & 1;
                const int row = 8 * (8 * a + 2 * (r >> 1) + par) + 2 * m + (r & 1);
                uint4 v; ldsm4t(v.x, v.y, v.z, v.w, sb + OFF_UT + row * 160 + cb * 16);
                g_uT[((tj * 80 + cb * 8 + g) * 2 + par) * 128 + ti * 8 + 4 * a + t] = v;
            }
        }
        bar_sync(2, 256);
        uint32_t su_target = 0;
        if (ta == 0) { su_target = ctr_arrive<16>(&g_ctrJ[tj * 32]); TSTAMP(16); }
        if (ta >= 128 && ta < 208) { const int q = ta - 128; *(uint4*)(smem + OFF_UT + (q >> 3) * 2176 + (q & 7) * 16) = make_uint4(0, 0, 0, 0); }
        #pragma unroll
        for (int k = 0; k < 3; k++) {
            if (k < nch) {
                const int cl = aw + 2 * k;
                unsigned char* pt = smem + OFF_PT + cl * PT_CH;
                float* red = (float*)pt + w * 644;
                const float dt = bf16r(expf(pdt[k]));
                float inv;
                {
                    const float lr2 = -(bf16r(expf(pl[k][0])) * dt) * 1.4426950408889634f, li = pl[k][1] * dt;
                    const float cr = pl[k][2], ci = pl[k][3];
                    const float mw = ex2f(lr2 * 64.f);
                    uint32_t e = __reduce_max_sync(0xffffffffu, __float_as_uint(fmaxf(fabsf(cr), fabsf(ci)))) >> 23;
                    e = min(max(e, 1u), 253u);
                    const float sc = __uint_as_float((254u - e) << 23);
                    inv = __uint_as_float(e << 23);
                    ((float4*)red)[lane] = make_float4(lr2, li, mw * __cosf(li * 64.f), mw * __sinf(li * 64.f));
                    ((float2*)(red + 128))[lane] = make_float2(cr * sc, ci * sc);
                    float v = ex2f(lr2 * 2048.f) * (cr * __cosf(li * 2048.f) - ci * __sinf(li * 2048.f));
                    #pragma unroll
                    for (int o = 16; o > 0; o >>= 1) v += __shfl_xor_sync(0xffffffffu, v, o);
                    if (lane == 0) red[640] = v;
                }
                __syncwarp();
                float d[5][4];
                #pragma unroll
                for (int q = 0; q < 5; q++) { d[q][0] = d[q][1] = d[q][2] = d[q][3] = 0.f; }
                const float gf = (float)g;
                #pragma unroll 1
                for (int ks = 0; ks < 4; ks++) {
                    uint32_t A[5][4], B[4][2];
                    #pragma unroll
                    for (int hh = 0; hh < 2; hh++) {
                        const int nl = 8 * ks + t + 4 * hh;
                        const float4 p4 = ((const float4*)red)[nl];
                        const float2 p2 = ((const float2*)(red + 128))[nl];
                        const cpx W = { p4.z, p4.w }, C = { p2.x, p2.y };
                        const float mg = ex2f(p4.x * gf), an = p4.y * gf;
                        cpx Y = { mg * __cosf(an), mg * __sinf(an) };
                        #pragma unroll
                        for (int s = 0; s < 4; s++) {
                            B[s][hh] = pack_f16(C.r * Y.r - C.i * Y.i, -(C.r * Y.i) - C.i * Y.r);
                            if (s < 3) Y = csq(Y);
                        }
                        const cpx X1 = cmul(Y, W);
                        cpx X2 = cmul(X1, W), X3 = cmul(X2, W);
                        A[0][2 * hh] = pack_f16(Y.r, Y.i); A[0][2 * hh + 1] = pack_f16(X1.r, X1.i);
                        #pragma unroll
                        for (int s = 0; s < 4; s++) {
                            A[1 + s][2 * hh] = pack_f16(X2.r, X2.i); A[1 + s][2 * hh + 1] = pack_f16(X3.r, X3.i);
                            if (s < 3) { X2 = csq(X2); X3 = csq(X3); }
                        }
                    }
                    mma_f16(d[0], A[0][0], A[0][1], A[0][2], A[0][3], B[0][0], B[0][1]);
                    #pragma unroll
                    for (int s = 0; s < 4; s++) mma_f16(d[1 + s], A[1 + s][0], A[1 + s][1], A[1 + s][2], A[1 + s][3], B[s][0], B[s][1]);
                }
                __syncwarp();
                #pragma unroll
                for (int q = 0; q < 5; q++) {
                    *(float2*)(red + 128 * q + 8 * g + 2 * t) = make_float2(d[q][0] * inv, d[q][1] * inv);
                    *(float2*)(red + 128 * q + 64 + 8 * g + 2 * t) = make_float2(d[q][2] * inv, d[q][3] * inv);
                }
                bar_sync(3 + aw, 128);
                __nv_bfloat16* Kb = (__nv_bfloat16*)(smem + OFF_KB + aw * KB_WG);
                {
                    const float* r0 = (const float*)pt;
                    const float s2 = 2.f * dt;
                    #pragma unroll
                    for (int q = 0; q < 5; q++) { const int x = tw + 128 * q; Kb[x] = __float2bfloat16_rn(((r0[x] + r0[644 + x]) + (r0[1288 + x] + r0[1932 + x])) * s2); }
                    if (tw == 0) Kb[640] = __float2bfloat16_rn(((r0[640] + r0[1284]) + (r0[1928] + r0[2572])) * s2);
                    if (tw == 1) Kb[641] = __float2bfloat16_rn(0.f);
                }
                bar_sync(3 + aw, 128);
                const unsigned short* Ks = (const unsigned short*)Kb;
                for (int qd = tw; qd < 576; qd += 128) {
                    const int row = qd / 36, i0 = 128 * row + 4 * (qd - row * 36) - 16;
                    uint32_t kvl[5];
                    #pragma unroll
                    for (int z = 0; z < 5; z++) {
                        const int i = i0 - 1 + z;
                        const int ib = (int)__bfloat16_as_ushort(__float2bfloat16_rn((float)i)) - 0x4300 + 128;
                        kvl[z] = Ks[i < 0 ? 641 : (i < 256 ? i : ib)];
                    }
                    *(uint4*)(pt + qd * 16) = make_uint4(kvl[1] | (kvl[0] << 16), kvl[2] | (kvl[1] << 16), kvl[3] | (kvl[2] << 16), kvl[4] | (kvl[3] << 16));
                }
                if (k == 0) {
                    fence_async_smem();
                    bar_sync(2, 256);
                    if (ta == 0) {
                        TSTAMP(17);
                        ctr_wait(&g_ctrJ[tj * 32], su_target);
                        mbar_arrive(bSu);
                        fence_async();
                        mbar_expect_tx(bUT, 10 * 2048);
                        #pragma unroll 1
                        for (int q = 0; q < 10; q++) bulk_g2s(sb + OFF_UT + q * 2176 + 128, g_uT + (ch0 * 2 + q) * 128, 2048, bUT);
                        TSTAMP(18);
                    }
                    __syncwarp();
                }
            }
        }
        bar_sync(3 + aw, 128);
        if (tw == 0) TSTAMP(19 + aw);
        mbar_wait(bUT, 0);
        asm volatile("setmaxnreg.inc.sync.aligned.u32 120;");
        if (tw == 0) TSTAMP(30 + aw);
        #pragma unroll 1
        for (int k = 0; k < nch; k++) {
            const int cl = aw + 2 * k;
            float acc[4][16];
            uint32_t A[3][8];
            const uint32_t tb = sb + OFF_PT + cl * PT_CH + (uint32_t)((g >> 2) * 144 + 8 + 4 * w + (g & 3) - 2 * t) * 4;
            const uint32_t db = desc_lo(sb + OFF_UT + cl * UT_CH, 2176);
            #define LOADA(q) { const int s_ = (q) >> 1, m0_ = (q) & 1, m1_ = 3 - m0_; \
                A[(q) % 3][0] = lds32(tb + (m0_ * 576 + 16 * s_ + 8) * 4);   A[(q) % 3][1] = lds32(tb + (m0_ * 576 + 288 + 16 * s_ + 8) * 4); \
                A[(q) % 3][2] = lds32(tb + (m0_ * 576 + 16 * s_) * 4);       A[(q) % 3][3] = lds32(tb + (m0_ * 576 + 288 + 16 * s_) * 4); \
                A[(q) % 3][4] = lds32(tb + (m1_ * 576 + 16 * s_ + 8) * 4);   A[(q) % 3][5] = lds32(tb + (m1_ * 576 + 288 + 16 * s_ + 8) * 4); \
                A[(q) % 3][6] = lds32(tb + (m1_ * 576 + 16 * s_) * 4);       A[(q) % 3][7] = lds32(tb + (m1_ * 576 + 288 + 16 * s_) * 4); }
            LOADA(0) LOADA(1)
            sfor<0, 16>([&](auto Q) {
                constexpr int q = Q.v, s = q >> 1, m0 = q & 1, m1 = 3 - m0;
                const uint32_t* a = A[q % 3];
                wg_fence();
                sfor<m0, 4>([&](auto C) { constexpr int c = C.v; wgmma_rs_n32<0, desc_hi(128, 0), 8 + 32 * (c - m0) - s>(acc[c], a[0], a[1], a[2], a[3], db, q != 0); });
                sfor<m1, 4>([&](auto C) { constexpr int c = C.v; wgmma_rs_n32<0, desc_hi(128, 0), 8 + 32 * (c - m1) - s>(acc[c], a[4], a[5], a[6], a[7], db, 1); });
                wg_commit();
                if constexpr (q + 2 < 16) { if constexpr (q > 0) wg_wait<1>(); LOADA(q + 2) }
            });
            wg_wait<0>();
            const int gam = g >> 2, chl = ti * 5 + cl;
            const int f = (((chl >> 3) & 3) << 1) | (chl & 1);
            uint32_t* yp = g_yX + ((tj * 16 + gam) * 80 + chl) * 64 + (((4 * w + (g & 3)) ^ f) << 2) + t;
            #define SVAL(T, p) (acc[(T) >> 2][4 * ((T) & 3) + (p)] + ((T) >= 2 ? acc[((T) - 2) >> 2][4 * (((T) - 2) & 3) + 2 + (p)] : 0.f))
            #pragma unroll
            for (int a = 0; a < 8; a++) {
                float y[2];
                #pragma unroll
                for (int p = 0; p < 2; p++) {
                    const float up = SVAL(2 * a + 1, p);
                    const float dn = a > 0 ? SVAL(2 * a - 1 < 0 ? 0 : 2 * a - 1, p) : 0.f;
                    y[p] = SVAL(2 * a, p) + __shfl_xor_sync(0xffffffffu, gam ? dn : up, 16);
                }
                yp[a * 2 * 80 * 64] = pack_bf16(y[0], y[1]);
            }
            if (tw == 0) TSTAMP(22 + cl);
        }
        uint4 uu[5], dd[5];
        #pragma unroll
        for (int k = 0; k < 5; k++) {
            const int chn = k < 4 ? 32 * (k >> 1) + 8 * t : 64 + 8 * (t & 1);
            const int chunk = k < 4 ? 2 * wa + (k & 1) : (wa & 3) + 8 * (wa >> 2) + 4 * (t >> 1);
            uu[k] = __ldg((const uint4*)(P.u + (ti * 128 + 16 * g + chunk) * 640 + tj * 80 + chn));
            dd[k] = __ldg((const uint4*)(P.dskip + tj * 80 + chn));
        }
        bar_sync(2, 256);
        if (ta == 0) {
            TSTAMP(27);
            const uint32_t tg = ctr_arrive<16>(&g_ctrJ[tj * 32 + 2]);
            ctr_wait(&g_ctrJ[tj * 32 + 2], tg);
            fence_async();
            mbar_expect_tx(bY, 20480);
            bulk_g2s(sb + OFF_UT, g_yX + (tj * 16 + ti) * 80 * 64, 20480, bY);
            TSTAMP(28);
        }
        __syncwarp();
        mbar_wait(bY, 0);
        {
            const int m = lane >> 3, r = lane & 7;
            #pragma unroll
            for (int k = 0; k < 5; k++) {
                const int lch = (k < 4 ? 32 * (k >> 1) + 8 * (r >> 1) : 64 + 8 * ((r >> 1) & 1)) + 2 * m + (r & 1);
                const int lck = k < 4 ? 2 * wa + (k & 1) : (wa & 3) + 8 * (wa >> 2) + 4 * (r >> 2);
                const int f = (((lch >> 3) & 3) << 1) | (lch & 1);
                uint4 y; ldsm4t(y.x, y.y, y.z, y.w, sb + OFF_UT + lch * 256 + ((lck ^ f) << 4));
                const int chn = k < 4 ? 32 * (k >> 1) + 8 * t : 64 + 8 * (t & 1);
                const int chunk = k < 4 ? 2 * wa + (k & 1) : (wa & 3) + 8 * (wa >> 2) + 4 * (t >> 1);
                y.x = hadd2_bf(y.x, hmul2_bf(uu[k].x, dd[k].x)); y.y = hadd2_bf(y.y, hmul2_bf(uu[k].y, dd[k].y));
                y.z = hadd2_bf(y.z, hmul2_bf(uu[k].z, dd[k].z)); y.w = hadd2_bf(y.w, hmul2_bf(uu[k].w, dd[k].w));
                *(uint4*)(P.out + (size_t)(ti * 128 + 16 * g + chunk) * 1280 + tj * 80 + chn) = y;
            }
        }
        if (ta == 0) TSTAMP(29);
    }
}

typedef CUresult (*EncodeFn)(CUtensorMap*, CUtensorMapDataType, cuuint32_t, void*, const cuuint64_t*, const cuuint64_t*, const cuuint32_t*, const cuuint32_t*,
                             CUtensorMapInterleave, CUtensorMapSwizzle, CUtensorMapL2promotion, CUtensorMapFloatOOBfill);

void make_map(EncodeFn enc, CUtensorMap* m, const void* p, int rank, const cuuint64_t* dims, const cuuint64_t* strides, const cuuint32_t* box, CUtensorMapSwizzle sw) {
    const cuuint32_t es[3] = {1, 1, 1};
    enc(m, CU_TENSOR_MAP_DATA_TYPE_BFLOAT16, rank, const_cast<void*>(p), dims, strides, box, es, CU_TENSOR_MAP_INTERLEAVE_NONE, sw,
        CU_TENSOR_MAP_L2_PROMOTION_NONE, CU_TENSOR_MAP_FLOAT_OOB_FILL_NONE);
}

}

extern "C" void kernel_launch(void* const* d_in, const int* in_sizes, int n_in, void* d_out, int out_size) {
    (void)in_sizes; (void)n_in; (void)out_size;
    static EncodeFn enc = nullptr;
    static int nsm = 0;
    if (!enc) {
        void* fn = nullptr; cudaDriverEntryPointQueryResult qr;
        cudaGetDriverEntryPoint("cuTensorMapEncodeTiled", &fn, cudaEnableDefault, &qr);
        enc = (EncodeFn)fn;
        int dev = 0; cudaGetDevice(&dev);
        cudaDeviceGetAttribute(&nsm, cudaDevAttrMultiProcessorCount, dev);
        cudaFuncSetAttribute(fused_kernel, cudaFuncAttributeMaxDynamicSharedMemorySize, SMEM_TOTAL);
    }
    Params P;
    P.u = (const __nv_bfloat16*)d_in[0]; P.logA = (const __nv_bfloat16*)d_in[1]; P.Aim = (const __nv_bfloat16*)d_in[2];
    P.Cre = (const __nv_bfloat16*)d_in[3]; P.Cim = (const __nv_bfloat16*)d_in[4]; P.logdt = (const __nv_bfloat16*)d_in[5];
    P.dskip = (const __nv_bfloat16*)d_in[6]; P.wo = (const __nv_bfloat16*)d_in[9]; P.out = (__nv_bfloat16*)d_out;
    { const cuuint64_t d[2] = {640, 2048}, s[1] = {1280}; const cuuint32_t b[2] = {64, 128}; make_map(enc, &P.mx, d_in[7], 2, d, s, b, CU_TENSOR_MAP_SWIZZLE_128B); }
    { const cuuint64_t d[3] = {640, 640, 3}, s[2] = {3840, 1280}; const cuuint32_t b[3] = {64, 64, 3}; make_map(enc, &P.mw64, d_in[8], 3, d, s, b, CU_TENSOR_MAP_SWIZZLE_128B); }
    { const cuuint64_t d[3] = {640, 640, 3}, s[2] = {3840, 1280}; const cuuint32_t b[3] = {16, 64, 3}; make_map(enc, &P.mw16, d_in[8], 3, d, s, b, CU_TENSOR_MAP_SWIZZLE_32B); }
    { const cuuint64_t d[2] = {640, 2048}, s[1] = {1280}; const cuuint32_t b[2] = {80, 128}; make_map(enc, &P.mu, d_in[0], 2, d, s, b, CU_TENSOR_MAP_SWIZZLE_NONE); }
    { const cuuint64_t d[2] = {1280, 2048}, s[1] = {2560}; const cuuint32_t b[2] = {80, 64}; make_map(enc, &P.mout, d_out, 2, d, s, b, CU_TENSOR_MAP_SWIZZLE_NONE); }
    P.use_smid = (nsm == 132);
    fused_kernel<<<P.use_smid ? 132 : 128, 512, SMEM_TOTAL>>>(P);
}
```

```cpp
#include <cuda_runtime.h>
#include <cuda.h>
#include <cuda_bf16.h>
#include <cuda_fp16.h>
#include <stdint.h>

extern __shared__ __align__(1024) unsigned char dsm[];

namespace {

constexpr int SLOT = 3072, SL_Y = 1280, SL_KV1 = 2560, SL_KV2 = 3040;
__device__ __align__(128) uint4    g_slot[128 * SLOT];
__device__ __align__(128) uint4    g_uT[640 * 2 * 128];
__device__ __align__(128) uint32_t g_ctrI[16 * 32];
__device__ __align__(128) uint32_t g_ctrJ[8 * 32];
#define TSTAMP(slot) do { } while (0)
#define TDUMP(lo, hi) do { } while (0)

struct Params {
    const __nv_bfloat16 *u, *logA, *Aim, *Cre, *Cim, *logdt, *dskip, *wo, *x, *wqkv;
    __nv_bfloat16* out;
    CUtensorMap mx, mw64, mw16, mout, mwo, mwo16, mout64, mut, mug, mout16;
};

constexpr int STAGE_B = 47104;
constexpr int OFF_G0  = 2 * STAGE_B;
constexpr int OFF_G2  = OFF_G0 + 53248;
constexpr int OFF_G1  = OFF_G2 + 28672;
constexpr int KB_CH   = 1376;
__host__ __device__ constexpr int off_kb(int k) { return k < 2 ? OFF_G2 - (2 - k) * KB_CH : k < 4 ? OFF_G1 + (k - 2) * KB_CH : OFF_G2 + (k - 4) * KB_CH; }
constexpr int UT_PAR  = (8 + 128) * 16;
constexpr int UT_CH   = 2 * UT_PAR;
constexpr int OFF_PT  = 186368;
constexpr int PT_CH   = 4480;
constexpr int OFF_US  = OFF_PT;
constexpr int OFF_UT  = 208896;
constexpr int OFF_KVB = OFF_PT - 20480;
constexpr int OFF_BAR = OFF_UT + 5 * UT_CH;
constexpr int SMEM_TOTAL = OFF_BAR + 640;
static_assert(SMEM_TOTAL <= 232448 && OFF_PT + 5 * PT_CH <= OFF_UT && OFF_G1 + 53248 <= OFF_BAR && OFF_US % 1024 == 0, "smem");
constexpr int OFF_PK  = 0;
constexpr int OFF_V   = 20480;
constexpr int OFF_WO  = 43008;
constexpr int OFF_OUTS = 0;
constexpr int SPIN_MAX = 1 << 20;
#define NCONV 5
#define UT_PACE 250
#define GO_K 6
#define YQ 2
#define PROD_END 8
#define PF_A 1
#define GO_SET 0
#define G2 0
#define G3 0
#define UT_GATE 5

__device__ __forceinline__ uint32_t smem_u32(const void* p) { return (uint32_t)__cvta_generic_to_shared(p); }
__device__ __forceinline__ void mbar_init(uint32_t bar, uint32_t cnt) { asm volatile("mbarrier.init.shared::cta.b64 [%0], %1;" :: "r"(bar), "r"(cnt) : "memory"); }
__device__ __forceinline__ void mbar_expect_tx(uint32_t bar, uint32_t bytes) { asm volatile("mbarrier.arrive.expect_tx.shared::cta.b64 _, [%0], %1;" :: "r"(bar), "r"(bytes) : "memory"); }
__device__ __forceinline__ void mbar_arrive(uint32_t bar) { asm volatile("mbarrier.arrive.shared::cta.b64 _, [%0];" :: "r"(bar) : "memory"); }
__device__ __forceinline__ void mbar_wait(uint32_t bar, uint32_t parity) {
    uint32_t done; int it = 0;
    do {
        asm volatile("{ .reg .pred p; mbarrier.try_wait.parity.shared::cta.b64 p, [%1], %2; selp.u32 %0, 1, 0, p; }" : "=r"(done) : "r"(bar), "r"(parity) : "memory");
        if (++it > SPIN_MAX) break;
    } while (!done);
}
__device__ __forceinline__ bool elect_one() { uint32_t p; asm volatile("{ .reg .pred q; elect.sync _|q, 0xffffffff; selp.u32 %0, 1, 0, q; }" : "=r"(p)); return p; }
__device__ __forceinline__ void bar_sync(int id, int n) { asm volatile("bar.sync %0, %1;" :: "r"(id), "r"(n) : "memory"); }
__device__ __forceinline__ void bar_dep(int id, int n, uint32_t v) { asm volatile("{ .reg .pred p, q; setp.eq.u32 q, %2, 0xFFFFFFFF; bar.red.or.pred p, %0, %1, q; }" :: "r"(id), "r"(n), "r"(v) : "memory"); }
__device__ __forceinline__ void bar_arrive(int id, int n) { asm volatile("bar.arrive %0, %1;" :: "r"(id), "r"(n) : "memory"); }
__device__ __forceinline__ void fence_async_smem() { asm volatile("fence.proxy.async.shared::cta;" ::: "memory"); }
__device__ __forceinline__ void tma2d(uint32_t dst, const CUtensorMap* m, uint32_t bar, int c0, int c1) {
    asm volatile("cp.async.bulk.tensor.2d.shared::cluster.global.mbarrier::complete_tx::bytes [%0], [%1, {%3, %4}], [%2];" :: "r"(dst), "l"(m), "r"(bar), "r"(c0), "r"(c1) : "memory");
}
__device__ __forceinline__ void tma5d(uint32_t dst, const CUtensorMap* m, uint32_t bar, int c0, int c1, int c2, int c3, int c4) {
    asm volatile("cp.async.bulk.tensor.5d.shared::cluster.global.mbarrier::complete_tx::bytes [%0], [%1, {%3, %4, %5, %6, %7}], [%2];" :: "r"(dst), "l"(m), "r"(bar), "r"(c0), "r"(c1), "r"(c2), "r"(c3), "r"(c4) : "memory");
}
__device__ __forceinline__ void tma3d_mc(uint32_t dst, const CUtensorMap* m, uint32_t bar, int c0, int c1, int c2, unsigned short mask) {
    asm volatile("cp.async.bulk.tensor.3d.shared::cluster.global.mbarrier::complete_tx::bytes.multicast::cluster [%0], [%1, {%3, %4, %5}], [%2], %6;" :: "r"(dst), "l"(m), "r"(bar), "r"(c0), "r"(c1), "r"(c2), "h"(mask) : "memory");
}
__device__ __forceinline__ void mbar_arrive2(uint32_t bar, uint32_t peer, uint32_t cnt) {
    asm volatile("{ .reg .b32 ra; mapa.shared::cluster.u32 ra, %0, %1; mbarrier.arrive.shared::cluster.b64 _, [ra], %2; mbarrier.arrive.shared::cta.b64 _, [%0], %2; }" :: "r"(bar), "r"(peer), "r"(cnt) : "memory");
}
__device__ __forceinline__ void bulk_g2s(uint32_t dst, const void* src, uint32_t bytes, uint32_t bar) {
    asm volatile("cp.async.bulk.shared::cluster.global.mbarrier::complete_tx::bytes [%0], [%1], %2, [%3];" :: "r"(dst), "l"(src), "r"(bytes), "r"(bar) : "memory");
}
__device__ __forceinline__ void bulk_s2g(void* dst, uint32_t src, uint32_t bytes) {
    asm volatile("cp.async.bulk.global.shared::cta.bulk_group [%0], [%1], %2;" :: "l"(dst), "r"(src), "r"(bytes) : "memory");
}
__device__ __forceinline__ void tma_st2d(const CUtensorMap* m, uint32_t src, int c0, int c1) {
    asm volatile("cp.async.bulk.tensor.2d.global.shared::cta.bulk_group [%0, {%2, %3}], [%1];" :: "l"(m), "r"(src), "r"(c0), "r"(c1) : "memory");
}
__device__ __forceinline__ void bulk_commit() { asm volatile("cp.async.bulk.commit_group;" ::: "memory"); }
__device__ __forceinline__ void bulk_wait_read() { asm volatile("cp.async.bulk.wait_group.read 0;" ::: "memory"); }
__device__ __forceinline__ void bulk_wait() { asm volatile("cp.async.bulk.wait_group 0;" ::: "memory"); }
__device__ __forceinline__ void wg_fence() { asm volatile("wgmma.fence.sync.aligned;" ::: "memory"); }
__device__ __forceinline__ void wg_commit() { asm volatile("wgmma.commit_group.sync.aligned;" ::: "memory"); }
template <int N> __device__ __forceinline__ void wg_wait() { asm volatile("wgmma.wait_group.sync.aligned %0;" :: "n"(N) : "memory"); }
__device__ __forceinline__ uint32_t desc_lo(uint32_t off, uint32_t lbo) { uint32_t b; asm("mov.u32 %0, dsm;" : "=r"(b)); return (((b & 0x3FFFF) + off) >> 4) | ((lbo >> 4) << 16); }
__host__ __device__ constexpr uint32_t desc_hi(uint32_t sbo, uint32_t sw) { return (sbo >> 4) | (sw << 30); }
template <int I> struct IC { static constexpr int v = I; };
template <int B, int E, class F> __device__ __forceinline__ void sfor(F&& f) { if constexpr (B < E) { f(IC<B>{}); sfor<B + 1, E>(f); } }
__device__ __forceinline__ void ldsm4t(uint32_t& r0, uint32_t& r1, uint32_t& r2, uint32_t& r3, uint32_t addr) {
    asm volatile("ldmatrix.sync.aligned.m8n8.x4.trans.shared.b16 {%0,%1,%2,%3}, [%4];" : "=r"(r0), "=r"(r1), "=r"(r2), "=r"(r3) : "r"(addr) : "memory");
}
__device__ __forceinline__ void stsm4(uint32_t addr, uint32_t r0, uint32_t r1, uint32_t r2, uint32_t r3) {
    asm volatile("stmatrix.sync.aligned.m8n8.x4.shared.b16 [%0], {%1,%2,%3,%4};" :: "r"(addr), "r"(r0), "r"(r1), "r"(r2), "r"(r3) : "memory");
}
__device__ __forceinline__ uint32_t lds32(uint32_t a) { uint32_t v; asm volatile("ld.shared.b32 %0, [%1];" : "=r"(v) : "r"(a) : "memory"); return v; }
__device__ __forceinline__ uint32_t pack_bf16(float lo, float hi) { uint32_t r; asm("cvt.rn.bf16x2.f32 %0, %1, %2;" : "=r"(r) : "f"(hi), "f"(lo)); return r; }
__device__ __forceinline__ uint32_t pack_f16(float lo, float hi) { uint32_t r; asm("cvt.rn.f16x2.f32 %0, %1, %2;" : "=r"(r) : "f"(hi), "f"(lo)); return r; }
__device__ __forceinline__ float bf_lo(uint32_t v) { return __uint_as_float(v << 16); }
__device__ __forceinline__ float bf_hi(uint32_t v) { return __uint_as_float(v & 0xFFFF0000u); }
__device__ __forceinline__ float bf16r(float x) { return __bfloat162float(__float2bfloat16_rn(x)); }
__device__ __forceinline__ float ex2f(float x) { float r; asm("ex2.approx.ftz.f32 %0, %1;" : "=f"(r) : "f"(x)); return r; }
__device__ __forceinline__ uint32_t hadd2_bf(uint32_t a, uint32_t b) { uint32_t r; asm("add.rn.bf16x2 %0, %1, %2;" : "=r"(r) : "r"(a), "r"(b)); return r; }

__device__ __forceinline__ uint32_t phi2(float a, float b) {
    const float pa = a > 0.f ? a + 1.f : ex2f(a * 1.4426950408889634f), pb = b > 0.f ? b + 1.f : ex2f(b * 1.4426950408889634f);
    return hadd2_bf(pack_bf16(pa, pb), 0x35863586u);
}

template <int OFF = 0> __device__ __forceinline__ uint4 ld_rlx4(const uint4* p) { uint4 v; asm volatile("ld.relaxed.gpu.global.v4.u32 {%0,%1,%2,%3}, [%4+%5];" : "=r"(v.x), "=r"(v.y), "=r"(v.z), "=r"(v.w) : "l"(p), "n"(OFF * 16) : "memory"); return v; }
template <int OFF = 0> __device__ __forceinline__ uint2 ld_rlx2(const uint2* p) { uint2 v; asm volatile("ld.relaxed.gpu.global.v2.u32 {%0,%1}, [%2+%3];" : "=r"(v.x), "=r"(v.y) : "l"(p), "n"(OFF * 8) : "memory"); return v; }
__device__ __forceinline__ uint32_t ld_rlx1(const uint32_t* p) { uint32_t v; asm volatile("ld.relaxed.gpu.global.u32 %0, [%1];" : "=r"(v) : "l"(p) : "memory"); return v; }
template <int OFF = 0> __device__ __forceinline__ void st_rlx4(uint4* p, uint4 v) { asm volatile("st.relaxed.gpu.global.v4.u32 [%0+%5], {%1,%2,%3,%4};" :: "l"(p), "r"(v.x), "r"(v.y), "r"(v.z), "r"(v.w), "n"(OFF * 16) : "memory"); }
template <int OFF = 0> __device__ __forceinline__ void st_rlx1(uint32_t* p, uint32_t v) { asm volatile("st.relaxed.gpu.global.u32 [%0+%2], %1;" :: "l"(p), "r"(v), "n"(OFF * 4) : "memory"); }
__device__ __forceinline__ void red_add(uint32_t* p) { asm volatile("red.relaxed.gpu.global.add.u32 [%0], 1;" :: "l"(p) : "memory"); }
__device__ __forceinline__ uint32_t max4(uint4 v) { return max(max(v.x, v.y), max(v.z, v.w)); }
template <int OFF = 0> __device__ __forceinline__ void st_rlx2(uint2* p, uint2 v) { asm volatile("st.relaxed.gpu.global.v2.u32 [%0+%3], {%1,%2};" :: "l"(p), "r"(v.x), "r"(v.y), "n"(OFF * 8) : "memory"); }
__device__ __forceinline__ uint32_t movm(uint32_t x) { uint32_t r; asm volatile("movmatrix.sync.aligned.m8n8.trans.b16 %0, %1;" : "=r"(r) : "r"(x)); return r; }
__device__ __forceinline__ uint32_t prmt(uint32_t a, uint32_t b, uint32_t c) { uint32_t r; asm("prmt.b32 %0, %1, %2, %3;" : "=r"(r) : "r"(a), "r"(b), "r"(c)); return r; }
__device__ __forceinline__ void pin(uint32_t& x) { asm volatile("" : "+r"(x)); }

template <int TB, uint32_t BHI, int BOFF> __device__ __forceinline__ void wgmma_rs_n32(float (&d)[16], uint32_t a0, uint32_t a1, uint32_t a2, uint32_t a3, uint32_t blo, int sd) {
    asm volatile("{ .reg .pred p; .reg .b32 lb; .reg .b64 db; setp.ne.b32 p, %21, 0; add.u32 lb, %20, %24; mov.b64 db, {lb, %23};\n"
        "wgmma.mma_async.sync.aligned.m64n32k16.f32.bf16.bf16 {%0, %1, %2, %3, %4, %5, %6, %7, %8, %9, %10, %11, %12, %13, %14, %15}, {%16, %17, %18, %19}, db, p, 1, 1, %22; }\n"
        : "+f"(d[0]), "+f"(d[1]), "+f"(d[2]), "+f"(d[3]), "+f"(d[4]), "+f"(d[5]), "+f"(d[6]), "+f"(d[7]), "+f"(d[8]), "+f"(d[9]), "+f"(d[10]), "+f"(d[11]), "+f"(d[12]), "+f"(d[13]), "+f"(d[14]), "+f"(d[15])
        : "r"(a0), "r"(a1), "r"(a2), "r"(a3), "r"(blo), "r"(sd), "n"(TB), "n"(BHI), "n"(BOFF));
}
template <int TB, uint32_t BHI, int BOFF> __device__ __forceinline__ void wgmma_rs_n48(float (&d)[24], uint32_t a0, uint32_t a1, uint32_t a2, uint32_t a3, uint32_t blo, int sd) {
    asm volatile("{ .reg .pred p; .reg .b32 lb; .reg .b64 db; setp.ne.b32 p, %29, 0; add.u32 lb, %28, %32; mov.b64 db, {lb, %31};\n"
        "wgmma.mma_async.sync.aligned.m64n48k16.f32.bf16.bf16 {%0, %1, %2, %3, %4, %5, %6, %7, %8, %9, %10, %11, %12, %13, %14, %15, %16, %17, %18, %19, %20, %21, %22, %23}, {%24, %25, %26, %27}, db, p, 1, 1, %30; }\n"
        : "+f"(d[0]), "+f"(d[1]), "+f"(d[2]), "+f"(d[3]), "+f"(d[4]), "+f"(d[5]), "+f"(d[6]), "+f"(d[7]), "+f"(d[8]), "+f"(d[9]), "+f"(d[10]), "+f"(d[11]), "+f"(d[12]), "+f"(d[13]), "+f"(d[14]), "+f"(d[15]), "+f"(d[16]), "+f"(d[17]), "+f"(d[18]), "+f"(d[19]), "+f"(d[20]), "+f"(d[21]), "+f"(d[22]), "+f"(d[23])
        : "r"(a0), "r"(a1), "r"(a2), "r"(a3), "r"(blo), "r"(sd), "n"(TB), "n"(BHI), "n"(BOFF));
}
template <int TA, int TB, uint32_t AHI, int AOFF, uint32_t BHI, int BOFF> __device__ __forceinline__ void wgmma_ss_n48(float (&d)[24], uint32_t alo, uint32_t blo, int sd) {
    asm volatile("{ .reg .pred p; .reg .b32 la, lb; .reg .b64 da, db; setp.ne.b32 p, %26, 0; add.u32 la, %24, %30; mov.b64 da, {la, %29}; add.u32 lb, %25, %32; mov.b64 db, {lb, %31};\n"
        "wgmma.mma_async.sync.aligned.m64n48k16.f32.bf16.bf16 {%0, %1, %2, %3, %4, %5, %6, %7, %8, %9, %10, %11, %12, %13, %14, %15, %16, %17, %18, %19, %20, %21, %22, %23}, da, db, p, 1, 1, %27, %28; }\n"
        : "+f"(d[0]), "+f"(d[1]), "+f"(d[2]), "+f"(d[3]), "+f"(d[4]), "+f"(d[5]), "+f"(d[6]), "+f"(d[7]), "+f"(d[8]), "+f"(d[9]), "+f"(d[10]), "+f"(d[11]), "+f"(d[12]), "+f"(d[13]), "+f"(d[14]), "+f"(d[15]), "+f"(d[16]), "+f"(d[17]), "+f"(d[18]), "+f"(d[19]), "+f"(d[20]), "+f"(d[21]), "+f"(d[22]), "+f"(d[23])
        : "r"(alo), "r"(blo), "r"(sd), "n"(TA), "n"(TB), "n"(AHI), "n"(AOFF), "n"(BHI), "n"(BOFF));
}
template <int TA, int TB, uint32_t AHI, int AOFF, uint32_t BHI, int BOFF> __device__ __forceinline__ void wgmma_ss_n80(float (&d)[40], uint32_t alo, uint32_t blo, int sd) {
    asm volatile("{ .reg .pred p; .reg .b32 la, lb; .reg .b64 da, db; setp.ne.b32 p, %42, 0; add.u32 la, %40, %46; mov.b64 da, {la, %45}; add.u32 lb, %41, %48; mov.b64 db, {lb, %47};\n"
        "wgmma.mma_async.sync.aligned.m64n80k16.f32.bf16.bf16 {%0, %1, %2, %3, %4, %5, %6, %7, %8, %9, %10, %11, %12, %13, %14, %15, %16, %17, %18, %19, %20, %21, %22, %23, %24, %25, %26, %27, %28, %29, %30, %31, %32, %33, %34, %35, %36, %37, %38, %39}, da, db, p, 1, 1, %43, %44; }\n"
        : "+f"(d[0]), "+f"(d[1]), "+f"(d[2]), "+f"(d[3]), "+f"(d[4]), "+f"(d[5]), "+f"(d[6]), "+f"(d[7]), "+f"(d[8]), "+f"(d[9]), "+f"(d[10]), "+f"(d[11]), "+f"(d[12]), "+f"(d[13]), "+f"(d[14]), "+f"(d[15]), "+f"(d[16]), "+f"(d[17]), "+f"(d[18]), "+f"(d[19]), "+f"(d[20]), "+f"(d[21]), "+f"(d[22]), "+f"(d[23]), "+f"(d[24]), "+f"(d[25]), "+f"(d[26]), "+f"(d[27]), "+f"(d[28]), "+f"(d[29]), "+f"(d[30]), "+f"(d[31]), "+f"(d[32]), "+f"(d[33]), "+f"(d[34]), "+f"(d[35]), "+f"(d[36]), "+f"(d[37]), "+f"(d[38]), "+f"(d[39])
        : "r"(alo), "r"(blo), "r"(sd), "n"(TA), "n"(TB), "n"(AHI), "n"(AOFF), "n"(BHI), "n"(BOFF));
}
template <int TA, int TB, uint32_t AHI, int AOFF, uint32_t BHI, int BOFF> __device__ __forceinline__ void wgmma_ss_n192(float (&d)[96], uint32_t alo, uint32_t blo, int sd) {
    asm volatile("{ .reg .pred p; .reg .b32 la, lb; .reg .b64 da, db; setp.ne.b32 p, %98, 0; add.u32 la, %96, %102; mov.b64 da, {la, %101}; add.u32 lb, %97, %104; mov.b64 db, {lb, %103};\n"
        "wgmma.mma_async.sync.aligned.m64n192k16.f32.bf16.bf16 {%0, %1, %2, %3, %4, %5, %6, %7, %8, %9, %10, %11, %12, %13, %14, %15, %16, %17, %18, %19, %20, %21, %22, %23, %24, %25, %26, %27, %28, %29, %30, %31, %32, %33, %34, %35, %36, %37, %38, %39, %40, %41, %42, %43, %44, %45, %46, %47, %48, %49, %50, %51, %52, %53, %54, %55, %56, %57, %58, %59, %60, %61, %62, %63, %64, %65, %66, %67, %68, %69, %70, %71, %72, %73, %74, %75, %76, %77, %78, %79, %80, %81, %82, %83, %84, %85, %86, %87, %88, %89, %90, %91, %92, %93, %94, %95}, da, db, p, 1, 1, %99, %100; }\n"
        : "+f"(d[0]), "+f"(d[1]), "+f"(d[2]), "+f"(d[3]), "+f"(d[4]), "+f"(d[5]), "+f"(d[6]), "+f"(d[7]), "+f"(d[8]), "+f"(d[9]), "+f"(d[10]), "+f"(d[11]), "+f"(d[12]), "+f"(d[13]), "+f"(d[14]), "+f"(d[15]), "+f"(d[16]), "+f"(d[17]), "+f"(d[18]), "+f"(d[19]), "+f"(d[20]), "+f"(d[21]), "+f"(d[22]), "+f"(d[23]), "+f"(d[24]), "+f"(d[25]), "+f"(d[26]), "+f"(d[27]), "+f"(d[28]), "+f"(d[29]), "+f"(d[30]), "+f"(d[31]), "+f"(d[32]), "+f"(d[33]), "+f"(d[34]), "+f"(d[35]), "+f"(d[36]), "+f"(d[37]), "+f"(d[38]), "+f"(d[39]), "+f"(d[40]), "+f"(d[41]), "+f"(d[42]), "+f"(d[43]), "+f"(d[44]), "+f"(d[45]), "+f"(d[46]), "+f"(d[47]), "+f"(d[48]), "+f"(d[49]), "+f"(d[50]), "+f"(d[51]), "+f"(d[52]), "+f"(d[53]), "+f"(d[54]), "+f"(d[55]), "+f"(d[56]), "+f"(d[57]), "+f"(d[58]), "+f"(d[59]), "+f"(d[60]), "+f"(d[61]), "+f"(d[62]), "+f"(d[63]), "+f"(d[64]), "+f"(d[65]), "+f"(d[66]), "+f"(d[67]), "+f"(d[68]), "+f"(d[69]), "+f"(d[70]), "+f"(d[71]), "+f"(d[72]), "+f"(d[73]), "+f"(d[74]), "+f"(d[75]), "+f"(d[76]), "+f"(d[77]), "+f"(d[78]), "+f"(d[79]), "+f"(d[80]), "+f"(d[81]), "+f"(d[82]), "+f"(d[83]), "+f"(d[84]), "+f"(d[85]), "+f"(d[86]), "+f"(d[87]), "+f"(d[88]), "+f"(d[89]), "+f"(d[90]), "+f"(d[91]), "+f"(d[92]), "+f"(d[93]), "+f"(d[94]), "+f"(d[95])
        : "r"(alo), "r"(blo), "r"(sd), "n"(TA), "n"(TB), "n"(AHI), "n"(AOFF), "n"(BHI), "n"(BOFF));
}

template <uint32_t HI, int OFF> __device__ __forceinline__ void wgmma_ss_n40_f16_tt(float (&d)[20], uint32_t alo, uint32_t blo, int sd) {
    asm volatile("{ .reg .pred p; .reg .b32 la, lb; .reg .b64 da, db; setp.ne.b32 p, %22, 0; add.u32 la, %20, %24; mov.b64 da, {la, %23}; add.u32 lb, %21, %24; mov.b64 db, {lb, %23};\n"
        "wgmma.mma_async.sync.aligned.m64n40k16.f32.f16.f16 {%0, %1, %2, %3, %4, %5, %6, %7, %8, %9, %10, %11, %12, %13, %14, %15, %16, %17, %18, %19}, da, db, p, 1, 1, 1, 1; }\n"
        : "+f"(d[0]), "+f"(d[1]), "+f"(d[2]), "+f"(d[3]), "+f"(d[4]), "+f"(d[5]), "+f"(d[6]), "+f"(d[7]), "+f"(d[8]), "+f"(d[9]), "+f"(d[10]), "+f"(d[11]), "+f"(d[12]), "+f"(d[13]), "+f"(d[14]), "+f"(d[15]), "+f"(d[16]), "+f"(d[17]), "+f"(d[18]), "+f"(d[19])
        : "r"(alo), "r"(blo), "r"(sd), "n"(HI), "n"(OFF));
}
__device__ __forceinline__ uint32_t hfma2(uint32_t a, uint32_t b, uint32_t c) { uint32_t r; asm("fma.rn.f16x2 %0, %1, %2, %3;" : "=r"(r) : "r"(a), "r"(b), "r"(c)); return r; }
__device__ __forceinline__ uint32_t hmul2(uint32_t a, uint32_t b) { uint32_t r; asm("mul.rn.f16x2 %0, %1, %2;" : "=r"(r) : "r"(a), "r"(b)); return r; }
__device__ __forceinline__ int pos_bits(int i) { return (int)__bfloat16_as_ushort(__float2bfloat16_rn((float)i)); }
__device__ __forceinline__ int kidx(int i) { return i < 256 ? max(i + 8, 2) : min(pos_bits(i) - 0x4300 + 136, 521); }

__device__ __forceinline__ float exp_acc(float x) { const float h = x * 1.4426950408889634f; const float l = fmaf(x, 1.4426950408889634f, -h) + x * 1.925963033500e-8f; return ex2f(h) * fmaf(l, 0.6931471805599453f, 1.f); }
struct cpx { float r, i; };
__device__ __forceinline__ cpx cmul(cpx a, cpx b) { return { a.r * b.r - a.i * b.i, a.r * b.i + a.i * b.r }; }
__device__ __forceinline__ cpx csq(cpx a) { return { a.r * a.r - a.i * a.i, (a.r + a.r) * a.i }; }
__device__ __forceinline__ cpx cexp_p(float lr2, float li, float p) { const float m = ex2f(lr2 * p), an = li * p; return { m * __cosf(an), m * __sinf(an) }; }

__device__ __forceinline__ void issue_stage(const Params& P, uint32_t sb, uint32_t bfull, int s, int kb, int ti, int tj, int rank, bool mc) {
    const uint32_t st = sb + s * STAGE_B, bar = bfull + 8 * s;
    const unsigned short mask = mc ? 3 : 1 << rank;
    if (elect_one()) {
        mbar_expect_tx(bar, STAGE_B);
        tma2d(st, &P.mx, bar, kb * 64, ti * 128);
    }
    #pragma unroll 1
    for (int h = rank; ; h ^= 1) {
        if (elect_one()) {
            tma3d_mc(st + 16384 + h * 12288, &P.mw64, bar, tj * 80, kb * 64 + h * 32, 0, mask);
            tma3d_mc(st + 40960 + h * 3072, &P.mw16, bar, tj * 80 + 64, kb * 64 + h * 32, 0, mask);
        }
        if (mc || h != rank) break;
    }
}

template <bool SMID>
__global__ void __cluster_dims__(2, 1, 1) __launch_bounds__(512, 1) fused_kernel(const __grid_constant__ Params P) {
    unsigned char* const smem = dsm;
    const uint32_t sb = smem_u32(smem);
    const int tid = threadIdx.x, lane = tid & 31;
    int ti, tj; bool spare = false;
    if (SMID) {
        uint32_t s; asm volatile("mov.u32 %0, %%smid;" : "=r"(s));
        const int q = ((int)s - 64) >> 1, q7 = (q * 37) >> 8;
        const int gp = s < 64 ? (s >> 1) & 7 : (s < 124 ? 1 + q - 7 * q7 : 0);
        tj = s < 64 ? s >> 4 : (s < 124 ? 4 + q7 : q - 26);
        ti = 2 * gp + (s & 1);
        spare = tj > 7;
    } else { ti = blockIdx.x & 15; tj = blockIdx.x >> 4; }
    const uint32_t bFull = sb + OFF_BAR, bSu = bFull + 32, bWo = bFull + 40, bO = bFull + 48, bGo = bFull + 56, bEmpty = bFull + 352, bOf = bFull + 384, bUT = bFull + 24;
    if (tid == 160) {
        mbar_init(bUT, 1); mbar_init(bSu, 2); mbar_init(bO, 8); mbar_init(bGo, 2);
        asm volatile("fence.mbarrier_init.release.cluster;" ::: "memory");
    }
    if (tid == 128) {
        mbar_init(bFull, 1); mbar_init(bFull + 8, 1); mbar_init(bFull + 16, 1); mbar_init(bWo, 2);
        mbar_init(bEmpty, 16); mbar_init(bEmpty + 8, 16); mbar_init(bEmpty + 16, 16);
        *(uint4*)(smem + OFF_BAR + 64) = make_uint4(0, tj, 0, 0);
        asm volatile("fence.mbarrier_init.release.cluster;" ::: "memory");
        asm volatile("fence.release.sync_restrict::shared::cta.cluster;" ::: "memory");
    }
    __syncwarp();
    asm volatile("barrier.cluster.arrive.relaxed.aligned;" ::: "memory");
    uint32_t rank; asm volatile("mov.u32 %0, %%cluster_ctarank;" : "=r"(rank));
    if (spare) {
        asm volatile("barrier.cluster.wait.acquire.aligned;" ::: "memory");
        if (tid < 16) {
            const uint32_t tg = (atomicAdd(&g_ctrI[tid * 32], 2) & ~15u) + 16;
            #pragma unroll 1
            for (int it = 0; it < SPIN_MAX && (int)(ld_rlx1(&g_ctrI[tid * 32]) - tg) < 0; it++) __nanosleep(200);
        }
        return;
    }
    const int tile = ti * 8 + tj;
    const int warp = __shfl_sync(0xffffffffu, tid >> 5, 0), wg = warp >> 2, w = warp & 3, tw = tid & 127;
    const int g = lane >> 2, t = lane & 3;
    const int ch0 = tj * 80 + ti;

    const int k0 = wg < 2 ? 2 * wg : 2 * wg - 3;
    unsigned short raw[2][6];
    {
        if (warp >= 6 && elect_one()) asm volatile("prefetch.tensormap [%0];" :: "l"(&P.mx + (warp - 6)) : "memory");
        uint32_t peer_tj = 0;
        if (warp == 4) {
            asm volatile("barrier.cluster.wait.acquire.aligned;" ::: "memory");
            asm volatile("{ .reg .b32 ra; mapa.shared::cluster.u32 ra, %1, %2; ld.shared::cluster.u32 %0, [ra]; }" : "=r"(peer_tj) : "r"(sb + OFF_BAR + 68), "r"(rank ^ 1u) : "memory");
            asm volatile("st.shared.u32 [%0], %1;" :: "r"(sb + OFF_BAR + 72), "r"((peer_tj == (uint32_t)tj) ? rank ^ 1u : rank) : "memory");
        }
        #pragma unroll
        for (int hc = 0; hc < 2; hc++) {
            const int ch = ch0 + 16 * (hc ? 4 : k0), o = ch * 128 + tw;
            if (hc == 0 || wg == 2) {
                asm volatile("ld.global.nc.u16 %0, [%1];" : "=h"(raw[hc][0]) : "l"(P.logA + o) : "memory");
                asm volatile("ld.global.nc.u16 %0, [%1];" : "=h"(raw[hc][1]) : "l"(P.Aim + o) : "memory");
                asm volatile("ld.global.nc.u16 %0, [%1];" : "=h"(raw[hc][2]) : "l"(P.Cre + o) : "memory");
                asm volatile("ld.global.nc.u16 %0, [%1];" : "=h"(raw[hc][3]) : "l"(P.Cim + o) : "memory");
                asm volatile("ld.global.nc.u16 %0, [%1];" : "=h"(raw[hc][4]) : "l"(P.logdt + ch) : "memory");
                asm volatile("ld.global.nc.u16 %0, [%1];" : "=h"(raw[hc][5]) : "l"(P.dskip + ch) : "memory");
            } else { raw[hc][0] = raw[hc][1] = raw[hc][2] = raw[hc][3] = raw[hc][4] = raw[hc][5] = 0; }
        }
        if (warp == 4) {
            bar_arrive(15, 64);
            const bool m = __shfl_sync(0xffffffffu, peer_tj, 0) == (uint32_t)tj;
            #pragma unroll 1
            for (int q = 0; q < 2; q++) issue_stage(P, sb, bFull, q, q, ti, tj, rank, m);
        }
        uint32_t* mx = (uint32_t*)(smem + OFF_BAR + 128 + wg * 32);
        #pragma unroll
        for (int hc = 0; hc < 2; hc++) {
            const uint32_t m = __reduce_max_sync(0xffffffffu, max(raw[hc][2] & 0x7FFFu, raw[hc][3] & 0x7FFFu));
            if (lane == 0) mx[hc * 4 + w] = m;
        }
        if (warp == 6 && elect_one()) asm volatile("cp.async.bulk.prefetch.L2.global [%0], %1;" :: "l"(P.u + tile * 10240), "r"(20480) : "memory");
    }
    auto pf_kb = [&](int kb) {
        const __nv_bfloat16* pf = lane < 16 ? P.x + (tile * 16 + lane) * 640 + kb * 64 : P.wqkv + kb * 64 * 1920 + (tile * 15 + lane - 16) * 64;
        if (lane < 31 && kb < 10) asm volatile("prefetch.global.L2 [%0];" :: "l"(pf) : "memory");
    };
    if (PF_A && wg == 0 && w < PF_A + 1) pf_kb(2 + w);
    #define PEER (*(volatile uint32_t*)(smem + OFF_BAR + 72))
    float* const s2s = (float*)(smem + OFF_BAR + 80);
    float* const last = (float*)(smem + OFF_BAR + 256);
    #pragma unroll 1
    for (int hc = 0; hc < (wg == 2 ? 2 : 1); hc++) {
        unsigned short rw[6];
        #pragma unroll
        for (int z = 0; z < 6; z++) rw[z] = hc ? raw[1][z] : raw[0][z];
        const int k = hc ? 4 : k0;
        const float dt = bf16r(exp_acc(__uint_as_float((uint32_t)rw[4] << 16)));
        const float lr2 = -(bf16r(exp_acc(__uint_as_float((uint32_t)rw[0] << 16))) * dt) * 1.4426950408889634f, li = __uint_as_float((uint32_t)rw[1] << 16) * dt;
        unsigned char* tab = smem + (hc ? OFF_G2 : (k0 & 2) ? OFF_G1 : OFF_G0) + tw * 16;
        {
            const cpx g1 = cexp_p(lr2, li, 8.f), W = cexp_p(lr2, li, 64.f);
            const cpx g2 = csq(g1), g3 = cmul(g2, g1), g4 = csq(g2), g5 = cmul(g4, g1), g6 = csq(g3), g7 = cmul(g4, g3);
            const uint4 Rr = make_uint4(pack_f16(1.f, g1.r), pack_f16(g2.r, g3.r), pack_f16(g4.r, g5.r), pack_f16(g6.r, g7.r));
            const uint4 Ri = make_uint4(pack_f16(0.f, g1.i), pack_f16(g2.i, g3.i), pack_f16(g4.i, g5.i), pack_f16(g6.i, g7.i));
            uint4* ap = (uint4*)(tab + (k & 1) * 16384);
            ap[0] = Rr; ap[128] = Ri;
            cpx Wj = W;
            #pragma unroll
            for (int j = 1; j < 4; j++) {
                const uint32_t wp = pack_f16(Wj.r, Wj.i), wr = prmt(wp, 0, 0x1010), wi = prmt(wp, 0, 0x3232), wn = wi ^ 0x80008000u;
                ap[256 * j]       = make_uint4(hfma2(Rr.x, wr, hmul2(Ri.x, wn)), hfma2(Rr.y, wr, hmul2(Ri.y, wn)), hfma2(Rr.z, wr, hmul2(Ri.z, wn)), hfma2(Rr.w, wr, hmul2(Ri.w, wn)));
                ap[256 * j + 128] = make_uint4(hfma2(Ri.x, wr, hmul2(Rr.x, wi)), hfma2(Ri.y, wr, hmul2(Rr.y, wi)), hfma2(Ri.z, wr, hmul2(Rr.z, wi)), hfma2(Ri.w, wr, hmul2(Rr.w, wi)));
                if (j < 3) Wj = cmul(Wj, W);
            }
        }
        if (hc == 0) bar_sync(2 + wg, 128);
        {
            const uint32_t e_ = min(max(max4(*(const uint4*)(smem + OFF_BAR + 128 + wg * 32 + hc * 16)) >> 7, 1u), 253u);
            if (tw == 0) { s2s[k] = 2.f * dt * __uint_as_float(e_ << 23); s2s[5 + k] = __uint_as_float((uint32_t)rw[5] << 16); }
            const float sc = __uint_as_float((254u - e_) << 23);
            const cpx C = { __uint_as_float((uint32_t)rw[2] << 16) * sc, __uint_as_float((uint32_t)rw[3] << 16) * sc };
            const cpx w1 = cexp_p(lr2, li, 1.f), h1 = cexp_p(lr2, li, 256.f), h4 = cexp_p(lr2, li, 1024.f);
            unsigned char* bt = tab + (hc ? 16384 : 32768);
            uint4* bp = (uint4*)(bt + (k & 1) * 12288);
            const cpx w2 = csq(w1);
            const cpx c1 = cmul(C, w1), c2 = cmul(C, w2), c3 = cmul(c1, w2), c4 = cmul(c2, w2), c5 = cmul(c3, w2), c6 = cmul(c4, w2), c7 = cmul(c5, w2);
            const uint4 Br = make_uint4(pack_f16(C.r, c1.r), pack_f16(c2.r, c3.r), pack_f16(c4.r, c5.r), pack_f16(c6.r, c7.r));
            const uint4 Bn = make_uint4(pack_f16(-C.i, -c1.i), pack_f16(-c2.i, -c3.i), pack_f16(-c4.i, -c5.i), pack_f16(-c6.i, -c7.i));
            bp[0] = Br; bp[128] = Bn;
            const cpx h2 = csq(h1), h3 = cmul(h2, h1);
            auto mulp = [&](uint32_t r, uint32_t n, uint32_t hr, uint32_t hi, uint32_t& ro, uint32_t& no) { ro = hfma2(r, hr, hmul2(n, hi)); no = hfma2(n, hr, hmul2(r, hi ^ 0x80008000u)); };
            const uint32_t p1 = pack_f16(h1.r, h1.i), p2 = pack_f16(h2.r, h2.i), p3 = pack_f16(h3.r, h3.i);
            const uint32_t r04 = prmt(Br.x, Br.z, 0x5410), n04 = prmt(Bn.x, Bn.z, 0x5410);
            uint4 Er, En;
            mulp(prmt(Br.x, Br.y, 0x5410), prmt(Bn.x, Bn.y, 0x5410), prmt(p1, 0, 0x1010), prmt(p1, 0, 0x3232), Er.x, En.x);
            mulp(prmt(Br.z, Br.w, 0x5410), prmt(Bn.z, Bn.w, 0x5410), prmt(p1, 0, 0x1010), prmt(p1, 0, 0x3232), Er.y, En.y);
            mulp(r04, n04, prmt(p2, 0, 0x1010), prmt(p2, 0, 0x3232), Er.z, En.z);
            mulp(r04, n04, prmt(p3, 0, 0x1010), prmt(p3, 0, 0x3232), Er.w, En.w);
            bp[256] = Er; bp[384] = En;
            const cpx j0 = cmul(C, h4);
            const uint32_t pj = pack_f16(j0.r, -j0.i), jr = prmt(pj, 0, 0x1010), jn = prmt(pj, 0, 0x3232);
            uint2 Jr, Jn;
            mulp(jr, jn, prmt(p1, 0x3C00u, 0x1054), prmt(p1, 0, 0x3254), Jr.x, Jn.x);
            mulp(jr, jn, prmt(p2, p3, 0x5410), prmt(p2, p3, 0x7632), Jr.y, Jn.y);
            *(uint2*)(bt + 8192 + (k & 1) * 8) = Jr;
            *(uint2*)(bt + 8192 + 2048 + (k & 1) * 8) = Jn;
            float v = j0.r * h4.r - j0.i * h4.i;
            #pragma unroll
            for (int o = 16; o > 0; o >>= 1) v += __shfl_xor_sync(0xffffffffu, v, o);
            if (lane == 0) last[k * 4 + w] = v;
        }
        if (wg != 3) { if (hc == 1) bar_arrive(9, 256); else bar_arrive(7, 512); }
    }
    if (warp != 4) asm volatile("barrier.cluster.wait.acquire.aligned;" ::: "memory");

    if (wg < 2) {
        asm volatile("setmaxnreg.inc.sync.aligned.u32 152;");
        if (elect_one()) { mbar_init(bOf + 24 * warp, 1); mbar_init(bOf + 24 * warp + 8, 1); mbar_init(bOf + 24 * warp + 16, 1); }
        bar_sync(1, 256);
        const uint32_t peer = __shfl_sync(0xffffffffu, PEER, 0);
        mbar_wait(bFull, 0);
        if (warp == 4) { mbar_wait(bEmpty + 16, 0); issue_stage(P, sb, bFull, 2, 2, ti, tj, rank, peer != rank); }
        bar_sync(8, 384);
        uint32_t pq[20];
        {
            float acc[96], acc2[24];
            #pragma unroll 1
            for (int kb = 0, s = 0, ph = 0, sp = 0; kb < 10; kb++) {
                if (kb) mbar_wait(bFull + 8 * s, ph);
                if (tid == 0 && kb == 0) TSTAMP(32);
                const uint32_t st = s * STAGE_B;
                const uint32_t da = desc_lo(st + wg * 8192, 16), db = desc_lo(st + 16384, 4096), dc = desc_lo(st + 40960, 1024);
                auto mma = [&](auto K) { constexpr int ks = K.v;
                    wgmma_ss_n192<0, 1, desc_hi(1024, 1), 2 * ks, desc_hi(1024, 1), 768 * (ks >> 1) + 128 * (ks & 1)>(acc, da, db, (kb | ks) != 0);
                    wgmma_ss_n48<0, 1, desc_hi(1024, 1), 2 * ks, desc_hi(256, 3), 192 * (ks >> 1) + 32 * (ks & 1)>(acc2, da, dc, (kb | ks) != 0);
                };
                wg_fence();
                mma(IC<0>{});
                wg_commit();
                wg_wait<1>();
                if (kb > 0 && elect_one()) mbar_arrive2(bEmpty + 8 * sp, peer, 1);
                wg_fence();
                sfor<1, 4>(mma);
                wg_commit();
                sp = s;
                if (++s == 3) { s = 0; ph ^= 1; }
            }
            if (tid == 0) TSTAMP(41);
            mbar_wait(bSu, 0);
            wg_wait<0>();
            if (elect_one()) mbar_arrive2(bEmpty, peer, 1);
            if (tid == 0) TSTAMP(0);
            uint32_t pk[20], vv[20];
            #pragma unroll
            for (int c = 0; c < 10; c++) {
                const float* V = c < 8 ? &acc[4 * (16 + c)] : &acc2[4 * (4 + c - 8)];
                vv[2 * c] = pack_bf16(V[0], V[1]); vv[2 * c + 1] = pack_bf16(V[2], V[3]);
                pin(vv[2 * c]); pin(vv[2 * c + 1]);
            }
            #pragma unroll
            for (int c = 0; c < 10; c++) {
                const float* K = c < 8 ? &acc[4 * (8 + c)] : &acc2[4 * (2 + c - 8)];
                pk[2 * c] = phi2(K[0], K[1]); pk[2 * c + 1] = phi2(K[2], K[3]);
                pin(pk[2 * c]); pin(pk[2 * c + 1]);
            }
            bar_sync(1, 256);
            {
                const uint32_t rowoff = (uint32_t)(wg * 64 + w * 16 + ((lane >> 3) & 1) * 8 + (lane & 7)) * 16;
                const int hi = lane >> 4;
                #pragma unroll
                for (int c = 0; c < 10; c += 2) {
                    stsm4(sb + OFF_PK + (c + hi) * 2048 + rowoff, pk[2 * c], pk[2 * c + 1], pk[2 * c + 2], pk[2 * c + 3]);
                    const int vb = c + hi + ((c + hi) >= 5 ? 1 : 0);
                    stsm4(sb + OFF_V + vb * 2048 + rowoff, vv[2 * c], vv[2 * c + 1], vv[2 * c + 2], vv[2 * c + 3]);
                }
                if (tid < 128) *(uint4*)(smem + OFF_V + 5 * 2048 + tid * 16) = make_uint4(0x3F803F80u, 0x3F803F80u, 0x3F803F80u, 0x3F803F80u);
            }
            float rem[8];
            #pragma unroll
            for (int e = 0; e < 8; e++) asm volatile("add.f32 %0, %1, 0f80000000;" : "=f"(rem[e]) : "f"(acc2[e]));
            asm volatile("setmaxnreg.dec.sync.aligned.u32 128;");
            bar_arrive(14, 384);
            fence_async_smem();
            bar_sync(1, 256);
            auto phiq = [&] {
                #pragma unroll
                for (int c = 0; c < 10; c++) {
                    const float* Q = c < 8 ? &acc[4 * c] : &rem[4 * (c - 8)];
                    pq[2 * c] = phi2(Q[0], Q[1]); pq[2 * c + 1] = phi2(Q[2], Q[3]);
                    pin(pq[2 * c]); pin(pq[2 * c + 1]);
                }
            };
            {
                float kv[24];
                const uint32_t da = desc_lo(OFF_PK + wg * 5 * 2048, 128), db = desc_lo(OFF_V + wg * 5 * 2048, 128);
                wg_fence();
                sfor<0, 8>([&](auto K) { constexpr int ks = K.v; wgmma_ss_n48<1, 1, desc_hi(2048, 0), 16 * ks, desc_hi(2048, 0), 16 * ks>(kv, da, db, ks != 0); });
                wg_commit();
                wg_wait<0>();
                uint4* pa = g_slot + tile * SLOT + SL_KV1 + (wg * 40 + w * 16 + g) * 4 + t;
                uint2* pb = (uint2*)(g_slot + tile * SLOT + SL_KV1 + 320) + (wg * 40 + w * 16 + g) * 4 + t;
                sfor<0, 2>([&](auto H) { constexpr int h = H.v;
                    const int d = w * 16 + g + 8 * h;
                    const bool hi = d >= 20;
                    float x[6];
                    #pragma unroll
                    for (int e = 0; e < 2; e++) {
                        const float t0 = kv[2 * h + e], t1 = kv[4 + 2 * h + e], t2 = kv[8 + 2 * h + e], t3 = kv[12 + 2 * h + e], t4 = kv[16 + 2 * h + e], t5 = kv[20 + 2 * h + e];
                        const float b0 = wg ? t1 : t0, b1 = wg ? t2 : t1, b2 = wg ? t3 : t2, b3 = wg ? t4 : t3, b4 = wg ? t5 : t4, z = wg ? t0 : t5;
                        x[e] = hi ? b3 : b0; x[2 + e] = hi ? b4 : b1; x[4 + e] = (hi == (t >= 2)) ? b2 : z;
                    }
                    if (d < 40) {
                        st_rlx4<32 * h>(pa, make_uint4(__float_as_uint(x[0]), __float_as_uint(x[1]), __float_as_uint(x[2]), __float_as_uint(x[3])));
                        st_rlx2<32 * h>(pb, make_uint2(__float_as_uint(x[4]), __float_as_uint(x[5])));
                    }
                });
            }
            if (tid == 0) TSTAMP(1);
            const bool reducer = warp == 3 || warp == 6;
            if (reducer && lane < 30) {
                const int e = wg * 30 + lane;
                const uint2* src = (const uint2*)(g_slot + tj * SLOT + SL_KV1) + (e < 40 ? ti * 40 + e : 640 - 40 + ti * 20 + e);
                uint2 v[16];
                #pragma unroll 1
                for (int it = 0; it < SPIN_MAX; it++) {
                    uint32_t m = 0;
                    sfor<0, 16>([&](auto R) { v[R.v] = ld_rlx2<R.v * 16 * SLOT>(src); });
                    #pragma unroll
                    for (int r = 0; r < 16; r++) m = max(m, max(v[r].x, v[r].y));
                    if (m != ~0u) break;
                }
                float sx = 0.f, sy = 0.f;
                #pragma unroll
                for (int r = 0; r < 16; r++) { sx += __uint_as_float(v[r].x); sy += __uint_as_float(v[r].y); }
                st_rlx1((uint32_t*)(g_slot + tile * SLOT + SL_KV2) + e, pack_bf16(sx, sy));
                if (tid == 96) TSTAMP(2);
            }
            __syncwarp();
            if (reducer && lane == 0) mbar_arrive(bGo);
            phiq();
        }
        const int dd = wg == 0 ? tw : (w == 3 ? tw - 32 : tw);
        if (warp != 3 && warp != 6 && dd < 80) {
            const int d = dd, src = d / 5, r = d - src * 5, h = d / 20;
            const uint4* kp = g_slot + (src * 8 + tj) * SLOT + SL_KV2;
            unsigned char* row = smem + OFF_KVB + d * 16;
            uint32_t dep = pq[0];
            #pragma unroll
            for (int e = 1; e < 20; e++) dep &= pq[e];
            dep = dep == ~0u;
            #pragma unroll
            for (int z = 1; z < 4; z++) {
                const int o = (h + z) & 3;
                if (wg == 0) { *(uint4*)(row + 3 * o * 1280) = make_uint4(dep, 0, 0, 0); *(uint4*)(row + (3 * o + 1) * 1280) = make_uint4(0, 0, 0, 0); }
                else if (z < 3) *(uint4*)(row + (((h & 2) ? -1 : 5) + 3 * z) * 1280) = make_uint4(dep, 0, 0, 0);
            }
            mbar_wait(bGo, 0);
            if (wg == 0) {
                uint4 v0, v1;
                #pragma unroll 1
                for (int it = 0; it < SPIN_MAX; it++) { v0 = ld_rlx4<0>(kp + 2 * r); v1 = ld_rlx4<1>(kp + 2 * r); if (max(max4(v0), max4(v1)) != ~0u) break; }
                *(uint4*)(row + 3 * h * 1280) = make_uint4(v0.x, v0.z, v1.x, v1.z);
                *(uint4*)(row + (3 * h + 1) * 1280) = make_uint4(v0.y, v0.w, v1.y, v1.w);
            } else {
                uint4 v;
                #pragma unroll 1
                for (int it = 0; it < SPIN_MAX; it++) { v = ld_rlx4(kp + 10 + r); if (max4(v) != ~0u) break; }
                *(uint4*)(row + ((h >> 1) * 6 + 2) * 1280) = (h & 1) ? make_uint4(0, 0, v.z, v.w) : make_uint4(v.x, v.y, 0, 0);
                const uint32_t z = (h & 1) ? (v.x & 0xFFFF0000u) : (v.z & 0xFFFFu);
                *(uint4*)(row + ((h >> 1) * 6 + 5) * 1280) = make_uint4(z, z, z, z);
            }
        }
        fence_async_smem();
        bar_sync(1, 256);
        if (tid == 0) TSTAMP(3);
        uint32_t fr[20];
        {
            float nd[2][24];
            const uint32_t db = desc_lo(OFF_KVB, 128);
            wg_fence();
            sfor<0, 6>([&](auto E) { constexpr int hf = E.v & 1, ks = (E.v >> 1) + 2 * hf;
                wgmma_rs_n48<1, desc_hi(1280, 0), 16 * ks + 480 * hf>(nd[hf], pq[4 * ks], pq[4 * ks + 1], pq[4 * ks + 2], pq[4 * ks + 3], db, E.v > 1); });
            wg_commit();
            wg_wait<0>();
            float rc[2][4];
            #pragma unroll
            for (int hd = 0; hd < 4; hd++)
                #pragma unroll
                for (int h = 0; h < 2; h++) { float r; asm("rcp.approx.ftz.f32 %0, %1;" : "=f"(r) : "f"(nd[hd >> 1][20 + 2 * h + (hd & 1)] + 1e-6f)); rc[h][hd] = r; }
            #pragma unroll
            for (int c = 0; c < 10; c++)
                #pragma unroll
                for (int h = 0; h < 2; h++) {
                    float r;
                    if (c == 2) r = t < 2 ? rc[h][0] : rc[h][1];
                    else if (c == 7) r = t < 2 ? rc[h][2] : rc[h][3];
                    else r = rc[h][(c * 8) / 20];
                    fr[2 * c + h] = pack_bf16(nd[c / 5][4 * (c % 5) + 2 * h] * r, nd[c / 5][4 * (c % 5) + 2 * h + 1] * r);
                    pin(fr[2 * c + h]);
                }
        }
        #pragma unroll
        for (int ks = 0; ks < 5; ks++) stsm4(sb + warp * 2560 + ((lane >> 3) & 1) * 1280 + (2 * ks + (lane >> 4)) * 128 + (lane & 7) * 16, fr[4 * ks], fr[4 * ks + 1], fr[4 * ks + 2], fr[4 * ks + 3]);
        fence_async_smem();
        __syncwarp();
        {
            float acc[40];
            const uint4* ox = g_slot + ti * 8 * SLOT + warp * 160;
            const uint32_t bo = bOf + 24 * warp;
            auto slot_off = [&](int q) { return (uint32_t)(q == 2 ? OFF_KVB : q * 20480); };
            auto fetch = [&](int q, int n) {
                mbar_expect_tx(bo + 8 * q, 2560);
                bulk_g2s(sb + slot_off(q) + warp * 2560, ox + (n < tj ? n : n + 1) * SLOT, 2560, bo + 8 * q);
            };
            {
                const bool el = elect_one();
                if (el) { bulk_s2g(g_slot + tile * SLOT + warp * 160, sb + warp * 2560, 2560); bulk_commit(); mbar_arrive(bO); }
                if (tid == 0) TSTAMP(4);
            }
            mbar_wait(bWo, 0);
            #pragma unroll 1
            for (int n = -1, q = 0, ph = 1, qp = 0; n < 7; n++) {
                if (n >= 0) mbar_wait(bo + 8 * q, ph);
                const uint32_t da = desc_lo(slot_off(q) + wg * 10240, 128), db = desc_lo(OFF_WO + (n < 0 ? tj : n < tj ? n : n + 1) * 5120, 40960);
                wg_fence();
                sfor<0, 5>([&](auto K) { constexpr int ks = K.v; wgmma_ss_n80<0, 1, desc_hi(1280, 0), 16 * ks, desc_hi(512, 2), 64 * ks>(acc, da, db, n >= 0 || ks > 0); });
                wg_commit();
                if (n < 0) {
                    const uint32_t tg = *(volatile uint32_t*)(smem + OFF_BAR + 76) << 4;
                    uint32_t* ctr = &g_ctrI[ti * 32 + 1 + (warp >> 1)];
                    if (elect_one()) { bulk_wait(); red_add(ctr); }
                    mbar_wait(bO, 0);
                    wg_wait<0>();
                    #pragma unroll 1
                    for (int it = 0; it < SPIN_MAX && (int)(ld_rlx1(ctr) - tg) < 0; it++) { }
                    if (elect_one()) { fetch(1, 0); fetch(2, 1); fetch(0, 2); }
                    if (tid == 0) TSTAMP(20);
                } else {
                    wg_wait<1>();
                    if (n >= 1 && n < 5 && elect_one()) fetch(qp, n + 2);
                    if (tid == 0 && (n == 0 || n == 3)) TSTAMP(11 + n / 3);
                }
                qp = q;
                if (q == 0) ph ^= 1;
                if (++q == 3) q = 0;
            }
            wg_wait<0>();
            if (tid == 0) TSTAMP(6);
            const uint32_t rowa = sb + warp * 2560 + (uint32_t)(((lane >> 3) & 1) * 8 + (lane & 7)) * 160 + (lane >> 4) * 16;
            #pragma unroll
            for (int c = 0; c < 10; c += 2) {
                const float* a = &acc[4 * c];
                stsm4(rowa + c * 16, pack_bf16(a[0], a[1]), pack_bf16(a[2], a[3]), pack_bf16(a[4], a[5]), pack_bf16(a[6], a[7]));
            }
            fence_async_smem();
            __syncwarp();
            if (elect_one()) {
                tma_st2d(&P.mout, sb + warp * 2560, 640 + tj * 80, ti * 128 + warp * 16);
                bulk_commit();
                bulk_wait_read();
                if (warp == 0) TSTAMP(7);
            }
        }
    } else {
        if (wg == 3) {
            asm volatile("setmaxnreg.dec.sync.aligned.u32 80;");
            bar_sync(7, 512);
            const uint32_t peer = PEER;
            const int hy = w >> 1;
            float e[12], e1[12];
            #pragma unroll 1
            for (int set = 0; set < 5; set++) {
                float d[20];
                if (set < 3) {
                    if (set == 2) bar_sync(9, 256);
                    const uint32_t da = desc_lo(set == 0 ? OFF_G0 : set == 1 ? OFF_G1 : OFF_G2, 128), db = da + (set < 2 ? 2048 : 1024);
                    if (set != 1) fence_async_smem();
                    wg_fence();
                    sfor<0, 16>([&](auto K) { wgmma_ss_n40_f16_tt<desc_hi(4096, 0), 16 * K.v>(d, da, db, K.v != 0); });
                    wg_commit();
                }
                if (set > 1) {
                    const int kc = min(2 * set - 4 + hy, 4);
                    const float s2 = s2s[kc];
                    unsigned char* kb = smem + (set == 2 ? off_kb(0) : set == 3 ? off_kb(2) : off_kb(4)) + hy * KB_CH;
                    #pragma unroll
                    for (int z = 0; z < 12; z++) e[z] *= s2;
                    if ((tw & 63) == 0) e[0] += s2s[5 + kc];
                    #pragma unroll
                    for (int h = 0; h < 2; h++) {
                        const int rho = 16 * (w & 1) + g + 8 * h;
                        *(uint32_t*)(kb + 16 + (8 * rho + 2 * t) * 2) = pack_bf16(e[2 * h], e[2 * h + 1]);
                        *(uint32_t*)(kb + (t < 2 ? 528 + (4 * rho + 2 * t) * 2 : 784 + ((t - 2) * 64 + 2 * rho) * 2)) = pack_bf16(e[4 + 2 * h], e[5 + 2 * h]);
                        const uint32_t v = pack_bf16(e[8 + 2 * h], e[9 + 2 * h]);
                        if ((t >> 1) == hy) {
                            const int y1 = 64 * (t & 1) + rho - 1, o = 1180 + ((y1 >> 1) & 1) * 144 - (y1 >> 2) * 4 + (y1 & 1) * 2;
                            *(unsigned short*)(kb + (y1 < 0 ? 1040 : o)) = (unsigned short)v; *(unsigned short*)(kb + o - 32) = (unsigned short)(v >> 16);
                        }
                    }
                    if ((tw & 63) == 0) {
                        *(uint4*)kb = make_uint4(0, 0, 0, 0);
                        const float4 l4 = *(const float4*)(last + kc * 4);
                        *(unsigned short*)(kb + 1202) = (unsigned short)pack_bf16(((l4.x + l4.y) + (l4.z + l4.w)) * s2, 0.f);
                        *(unsigned short*)(kb + 1042) = 0; *(uint4*)(kb + 1184) = make_uint4(0, 0, 0, 0); *(uint4*)(kb + 1328) = make_uint4(0, 0, 0, 0);
                    }
                }
                wg_wait<0>();
                if (set == 0 && elect_one()) mbar_arrive2(bEmpty + 16, peer, 2);
                if (set == GO_SET) bar_arrive(8, 384);
                if (set == 1) bar_arrive(12, 224);
                if (set) bar_sync(5, 128);
                #pragma unroll
                for (int z = 0; z < 12; z++) { e[z] = e1[z]; e1[z] = z < 8 ? (hy ? d[12 + z] : d[z]) : d[z]; }
            }
            if (tw == 0) TSTAMP(47);
            bar_arrive(11, 192);
            #pragma unroll 1
            for (int e = 4 * tw; e < 848; e += 512) {
                const int row = e / 144, r4 = (e - 576) / 40;
                const bool lin = e >= 576 && e < 736;
                const int i = e < 576 ? e - 16 * row - 16 : lin ? e - 188 - 8 * r4 : e < 768 ? e - 240 : e < 800 ? e - 144 : e + 208;
                int x[5];
                #pragma unroll
                for (int z = 0; z < 5; z++) x[z] = lin ? i - 1 + z : kidx(i - 1 + z);
                const int A0 = x[2] & ~1;
                #pragma unroll
                for (int z = 0; z < 5; z++) x[z] = 0x22 * (x[z] - A0);
                const uint32_t s0 = 0x5454 + x[1] + (x[0] << 8), s1 = 0x5454 + x[2] + (x[1] << 8), s2 = 0x1010 + x[3] + (x[2] << 8), s3 = 0x1010 + x[4] + (x[3] << 8);
                uint32_t W[5][3];
                #pragma unroll
                for (int k = 0; k < 5; k++) { const uint32_t* wp = (const uint32_t*)(smem + off_kb(k) + 2 * A0 - 4); W[k][0] = wp[0]; W[k][1] = wp[1]; W[k][2] = wp[2]; }
                #pragma unroll
                for (int k = 0; k < 5; k++)
                    *(uint4*)(smem + OFF_PT + k * PT_CH + e * 4) = make_uint4(prmt(W[k][0], W[k][1], s0), prmt(W[k][0], W[k][1], s1), prmt(W[k][1], W[k][2], s2), prmt(W[k][1], W[k][2], s3));
            }
            bar_arrive(6, 256);
            bar_sync(13, 192);
            if (tw == 0) { mbar_arrive(bSu); TSTAMP(19); }
            if (w == 0) {
                const bool mc = __shfl_sync(0xffffffffu, PEER, 0) != rank;
                #pragma unroll 1
                for (int it = 0; it < SPIN_MAX && *(volatile uint32_t*)(smem + OFF_BAR + 64) < 7; it++) __nanosleep(100);
                #pragma unroll 1
                for (int z = 1; z >= 0; z--) {
                    mbar_wait(bEmpty + 16 * z, 1);
                    if (elect_one()) mbar_expect_tx(bWo, z ? 40960 : 61440);
                    #pragma unroll 1
                    for (int h = rank; ; h ^= 1) {
                        if (elect_one()) {
                            tma3d_mc(sb + OFF_WO + z * 40960 + h * 20480, &P.mwo, bWo, tj * 80 + z * 32, 0, 2 * h, mc ? 3 : 1 << rank);
                            if (z == 0) tma3d_mc(sb + OFF_WO + 81920 + h * 20480, &P.mwo16, bWo, tj * 80 + 64, 0, 2 * h, mc ? 3 : 1 << rank);
                        }
                        if (mc || h != rank) break;
                    }
                }
            }
            bar_sync(14, 384);
            asm volatile("setmaxnreg.inc.sync.aligned.u32 128;");
        } else {
            if (w == 3) {
                if (elect_one()) asm volatile("cp.async.bulk.prefetch.L2.global [%0], %1;" :: "l"(P.wo + tile * 3200), "r"(6400) : "memory");
                bar_sync(15, 64);
                const bool mc = __shfl_sync(0xffffffffu, PEER, 0) != rank;
                #pragma unroll 1
                for (int kb = 1, sp = 0, ph = 0; kb < PROD_END; kb++) {
                    mbar_wait(bEmpty + 8 * sp, ph);
                    if (kb < 8) issue_stage(P, sb, bFull, sp, kb + 2, ti, tj, rank, mc);
                    if (PF_A) pf_kb(kb + 2 + PF_A);
                    *(volatile uint32_t*)(smem + OFF_BAR + 64) = kb;
                    if (sp == 1) ph ^= 1;
                    if (++sp == 3) sp = 0;
                }
            } else {
                {
                    uint4 ub[16];
                    const __nv_bfloat16* p0 = P.u + (ti * 128 + 4 * (g >> 1) + (g & 1) + (w < 2 ? 0 : 2 * (t >> 1))) * 640 + tj * 80 + 32 * w + 8 * (w < 2 ? t : t & 1);
                    sfor<0, 16>([&](auto C) { constexpr int c = C.v; if (w < 2 || c < 8)
                        asm volatile("ld.global.nc.v4.u32 {%0,%1,%2,%3}, [%4+%5];" : "=r"(ub[c].x), "=r"(ub[c].y), "=r"(ub[c].z), "=r"(ub[c].w) : "l"(p0), "n"(((c & 7) * 16 + (c >> 3) * 2) * 1280) : "memory"); });
                    const int m = lane >> 3, r = lane & 7;
                    const int R = m * 40 + 8 * w + (w < 2 ? r : (r & 3) + (r >> 2) * 20);
                    const uint32_t da = sb + OFF_UT + R * 128;
                    if (w == 2) {
                        mbar_wait(bEmpty + 16, 0);
                        #pragma unroll 1
                        for (int i = lane; i < 1024; i += 32) { st_rlx4(g_slot + tile * SLOT + 2048 + i, make_uint4(~0u, ~0u, ~0u, ~0u)); __nanosleep(20); }
                    }
                    bar_sync(12, 224);
                    #pragma unroll
                    for (int c = 0; c < 16; c++) if (w < 2 || c < 8)
                        asm volatile("stmatrix.sync.aligned.m8n8.x4.trans.shared.b16 [%0], {%1,%2,%3,%4};" :: "r"(da + (c >> 3) * 2560 + (((c & 7) ^ ((R + 4 * (c >> 3)) & 7)) << 4)), "r"(ub[c].x), "r"(ub[c].y), "r"(ub[c].z), "r"(ub[c].w) : "memory");
                }
                fence_async_smem();
                if (w == 0) {
                    bar_sync(10, 96);
                    if (lane == 0) {
                        TSTAMP(44);
                        #pragma unroll 1
                        for (int q = 0; q < 4; q++) {
                            asm volatile("cp.async.bulk.tensor.5d.global.shared::cta.bulk_group [%0, {%2, %3, %4, %3, %5}], [%1];" :: "l"(&P.mut), "r"(sb + OFF_UT + q * 5120), "r"(ti * 64), "r"(0), "r"(tj * 10), "r"(q) : "memory");
                            bulk_commit(); if (q < 3) __nanosleep(UT_PACE);
                        }
                        bulk_wait();
                        TSTAMP(16);
                        const uint32_t tg = (atomicAdd(&g_ctrJ[tj * 32], 1) & ~15u) + 16;
                        #pragma unroll 1
                        for (int it = 0; it < SPIN_MAX && (int)(ld_rlx1(&g_ctrJ[tj * 32]) - tg) < 0; it++) __nanosleep(100);
                        TSTAMP(17);
                        #pragma unroll 1
                        for (int it = 0; it < SPIN_MAX && *(volatile uint32_t*)(smem + OFF_BAR + 64) <= UT_GATE; it++) __nanosleep(50);
                        mbar_expect_tx(bUT, 5 * UT_CH);
                        tma5d(sb + OFF_UT, &P.mug, bUT, 0, -1, 0, ti, tj * 5);
                    }
                    __syncwarp();
                } else {
                    bar_arrive(10, 96);
                    uint32_t tg = 0;
                    if (tw == 64) {
                        asm volatile("fence.acq_rel.gpu;" ::: "memory");
                        tg = (atomicAdd(&g_ctrJ[tj * 32 + 2], 1) & ~15u) + 16;
                        if (SMID) red_add(&g_ctrI[ti * 32]);
                    }
                    bar_sync(11, 192);
                    {
                        const int n1 = tw - 32;
                        uint4 xv[5];
                        #pragma unroll
                        for (int k = 0; k < 5; k++) { const uint32_t* wp = (const uint32_t*)(smem + off_kb(k) + 1180 + (n1 & 1) * 144 - (n1 >> 1) * 4); xv[k] = make_uint4(wp[0], wp[1], wp[2], wp[3]); }
                        #pragma unroll
                        for (int k = 0; k < 5; k++) *(uint4*)(smem + OFF_PT + k * PT_CH + 3408 + n1 * 16) = xv[k];
                        if (n1 < 5) *(uint4*)(smem + OFF_PT + n1 * PT_CH + 3392) = make_uint4(0, 0, 0, 0);
                        fence_async_smem();
                        bar_arrive(13, 192);
                    }
                    if (w == 2) {
                        if (lane == 0) {
                            #pragma unroll 1
                            for (int it = 0; it < SPIN_MAX && (int)(ld_rlx1(&g_ctrJ[tj * 32 + 2]) - tg) < 0; it++) __nanosleep(100);
                            *(volatile uint32_t*)(smem + OFF_BAR + 76) = tg >> 4;
                            mbar_arrive(bSu);
                        }
                        __syncwarp();
                    }
                }
            }
            bar_sync(6, 256);
        }
        const int gam = g >> 2, d0 = 4 * w + (g & 3) - 4 * t;
        uint32_t sel4[2], o4, bx[3][2];
        {
            int b4[4];
            #pragma unroll
            for (int z = 0; z < 4; z++) { const int d = d0 - z; b4[z] = (d + 1 + ((d >> 2) & 1)) >> 2; }
            sel4[0] = 0x1010 + 0x2200 * (b4[0] - b4[1]); sel4[1] = 0x1010 + 0x22 * (b4[0] - b4[2]) + 0x2200 * (b4[0] - b4[3]);
            o4 = (uint32_t)(580 + gam * 40 + b4[0]) * 4;
            #pragma unroll
            for (int sg = 0; sg < 3; sg++)
                #pragma unroll
                for (int h = 0; h < 2; h++) {
                    const uint32_t b = (uint32_t)(((h ? 0x1FF000ull : 0xFE0ull) << 15) >> (16 * sg + d0 + 12)) & 15u;
                    bx[sg][h] = 0x44444444u - 0x34u * (((b >> 3) & 1u) | ((b & 4u) << 6) | ((b & 2u) << 15) | ((b & 1u) << 24));
                }
        }
        mbar_wait(bUT, 0);
        if (tw == 0) TSTAMP(28 + wg);
        #pragma unroll 1
        for (int cl = wg - 2; cl < NCONV; cl += 2) {
            float acc[4][16];
            uint32_t A[6][4], Bx[3][4], E[4], Wf[2][4];
            const uint32_t tbase = sb + OFF_PT + cl * PT_CH;
            const uint32_t tp = tbase + (uint32_t)(gam * 144 + 14 + d0) * 4, t4 = tbase + o4, ts = tbase + (uint32_t)(750 + d0) * 4;
            const uint32_t db = desc_lo(OFF_UT + cl * UT_CH, UT_PAR), dx = desc_lo(OFF_PT + cl * PT_CH + 3392, 16);
            constexpr uint32_t HI = desc_hi(128, 0);
            #define LOADA(q) { uint32_t* a_ = A[(q) % 6]; constexpr int s_ = (q) >> 1; \
                if constexpr (((q) & 1) == 0) { a_[0] = lds32(tp + (16 * s_ + 2) * 4); a_[1] = lds32(tp + (288 + 16 * s_ + 2) * 4); a_[2] = lds32(tp + 16 * s_ * 4); a_[3] = lds32(tp + (288 + 16 * s_) * 4); } \
                else { \
                    if constexpr (s_ == 0) { a_[0] = lds32(ts + gam * 128 + 8); a_[2] = lds32(ts + gam * 128); } else a_[0] = lds32(t4 + 4 * s_ * 4); \
                    a_[1] = lds32(t4 + (80 + 4 * s_) * 4); \
                } }
            #define EXPAND(x, y, sel) { y = prmt(x, 0, sel[1]); x = prmt(x, 0, sel[0]); }
            #pragma unroll
            for (int sg = 0; sg < 3; sg++) { Bx[sg][0] = prmt(0x3F80u, 0, bx[sg][0]); Bx[sg][1] = prmt(0x3F80u, 0, bx[sg][1]); Bx[sg][2] = prmt(0x3F80u, 0, bx[sg][0] >> 16); Bx[sg][3] = prmt(0x3F80u, 0, bx[sg][1] >> 16); }
            wg_fence();
            sfor<0, 6>([&](auto Z) { constexpr int sg = Z.v >> 1, c = Z.v & 1; wgmma_rs_n32<0, HI, 8 + 32 * c - sg>(acc[c], Bx[sg][0], Bx[sg][1], Bx[sg][2], Bx[sg][3], db, sg != 0); });
            wg_commit();
            LOADA(0) LOADA(1) LOADA(2) LOADA(3)
            wg_wait<0>();
            #pragma unroll
            for (int th = 0; th < 2; th++)
                #pragma unroll
                for (int h = 0; h < 2; h++) {
                    float v[4];
                    #pragma unroll
                    for (int z = 0; z < 4; z++) v[z] = gam ? acc[th][8 * h + 4 + z] : acc[th][8 * h + z];
                    Wf[th][h] = pack_bf16(v[1], v[3]); Wf[th][2 + h] = pack_bf16(v[0], v[2]);
                }
            sfor<0, 8>([&](auto S) {
                constexpr int s = S.v;
                uint32_t* a = A[(2 * s) % 6]; uint32_t* b = A[(2 * s + 1) % 6];
                if constexpr (s > 0) EXPAND(b[0], b[2], sel4)
                EXPAND(b[1], b[3], sel4)
                if constexpr (s == 4 || s == 6) { E[0] = gam ? 0u : E[0]; E[2] = gam ? 0u : E[2]; E[1] = E[3] = 0u; }
                wg_fence();
                sfor<0, 4>([&](auto C) { constexpr int c = C.v; wgmma_rs_n32<0, HI, 8 + 32 * c - s>(acc[c], a[0], a[1], a[2], a[3], db, s != 0); });
                sfor<1, 4>([&](auto C) { constexpr int c = C.v; wgmma_rs_n32<0, HI, 8 + 32 * (c - 1) - s>(acc[c], b[0], b[1], b[2], b[3], db, 1); });
                if constexpr (s == 0) { wgmma_rs_n32<0, HI, 0>(acc[2], Wf[0][0], Wf[0][1], Wf[0][2], Wf[0][3], dx, 1); wgmma_rs_n32<0, HI, 32>(acc[3], Wf[0][0], Wf[0][1], Wf[0][2], Wf[0][3], dx, 1);
                                        wgmma_rs_n32<0, HI, 0>(acc[3], Wf[1][0], Wf[1][1], Wf[1][2], Wf[1][3], dx, 1); }
                if constexpr (s == 4 || s == 6) {
                    wgmma_rs_n32<0, HI, 8 - (s - 4) / 2>(acc[2], E[0], E[1], E[2], E[3], db, 1); wgmma_rs_n32<0, HI, 40 - (s - 4) / 2>(acc[3], E[0], E[1], E[2], E[3], db, 1); }
                wg_commit();
                if constexpr (s + 2 < 8) { wg_wait<1>(); LOADA(2 * s + 4) LOADA(2 * s + 5) }
                if constexpr (s == 2 || s == 5) { E[0] = lds32(ts + 256 + (s / 5) * 64 + 8); E[2] = lds32(ts + 256 + (s / 5) * 64); }
                if constexpr (s == YQ) { if (cl >= 2 && elect_one()) { bulk_wait(); red_add(&g_ctrJ[tj * 32 + 1]); } }
            });
            wg_wait<0>();
            uint32_t y[8];
            #define SVAL(T, p) (acc[(T) >> 2][4 * ((T) & 3) + (p)] + ((T) >= 2 ? acc[((T) >= 2 ? (T) - 2 : 0) >> 2][4 * (((T) - 2) & 3) + 2 + (p)] : 0.f))
            sfor<0, 8>([&](auto AA) { constexpr int a = AA.v;
                float f[2];
                #pragma unroll
                for (int p = 0; p < 2; p++) {
                    const float up = SVAL(2 * a + 1, p);
                    const float dn = a > 0 ? SVAL((a > 0 ? 2 * a - 1 : 0), p) : 0.f;
                    f[p] = SVAL(2 * a, p) + __shfl_xor_sync(0xffffffffu, gam ? dn : up, 16);
                }
                y[a] = pack_bf16(f[0], f[1]);
            });
            if (cl < 3) {
                bar_sync(2 + wg, 128);
                const uint32_t ys = tbase + w * 1024;
                stsm4(ys + lane * 16, y[0], y[1], y[2], y[3]); stsm4(ys + 512 + lane * 16, y[4], y[5], y[6], y[7]);
                fence_async_smem();
                __syncwarp();
                if (elect_one()) { bulk_s2g(g_slot + tile * SLOT + SL_Y + cl * 256 + w * 64, ys, 1024); bulk_commit(); }
            } else {
                uint32_t* yp = (uint32_t*)(g_slot + tile * SLOT + SL_Y + cl * 256 + w * 64) + lane;
                sfor<0, 8>([&](auto AA) { st_rlx1<AA.v * 32>(yp, y[AA.v]); });
            }
            if (tw == 0) TSTAMP(22 + cl);
        }
        if (NCONV == 5) {
            const uint4* p = g_slot + (g * 8 + tj) * SLOT + SL_Y + w * 64 + ti * 4 + t;
            const int row = 32 * (lane >> 3) + 16 * (lane & 1) + 4 * w + ((lane >> 1) & 3);
            #define STSMT(addr, v) asm volatile("stmatrix.sync.aligned.m8n8.x4.trans.shared.b16 [%0], {%1,%2,%3,%4};" :: "r"(addr), "r"((v).x), "r"((v).y), "r"((v).z), "r"((v).w) : "memory")
            if (wg == 3) {
                const uint32_t tg = *(volatile uint32_t*)(smem + OFF_BAR + 76) * 192;
                #pragma unroll 1
                for (int it = 0; it < SPIN_MAX && (int)(ld_rlx1(&g_ctrJ[tj * 32 + 1]) - tg) < 0; it++) __nanosleep(40);
                if (tw == 0) TSTAMP(15);
                uint4 v[8];
                sfor<0, 8>([&](auto B) { constexpr int b = B.v; v[b] = ld_rlx4<(b & 1) * 64 * SLOT + (b >> 1) * 256>(p); });
                bar_sync(5, 128);
                #pragma unroll
                for (int b = 0; b < 6; b++) STSMT(sb + OFF_PT + row * 128 + ((b ^ (row & 7)) << 4), v[b]);
                #pragma unroll 1
                for (int it = 0; it < SPIN_MAX && __any_sync(0xffffffffu, max(max4(v[6]), max4(v[7])) == ~0u); it++) { v[6] = ld_rlx4<768>(p); v[7] = ld_rlx4<64 * SLOT + 768>(p); }
                #pragma unroll
                for (int b = 6; b < 8; b++) STSMT(sb + OFF_PT + row * 128 + ((b ^ (row & 7)) << 4), v[b]);
            } else {
                uint4 f0, f1;
                #pragma unroll 1
                for (int it = 0; it < SPIN_MAX; it++) { f0 = ld_rlx4<1024>(p); f1 = ld_rlx4<64 * SLOT + 1024>(p); if (!__any_sync(0xffffffffu, max(max4(f0), max4(f1)) == ~0u)) break; }
                STSMT(sb + OFF_UT + row * 32, f0);
                STSMT(sb + OFF_UT + row * 32 + 16, f1);
            }
            fence_async_smem();
            bar_sync(2 + wg, 128);
            if (w == 0 && elect_one()) {
                tma_st2d(wg == 3 ? &P.mout64 : &P.mout16, sb + (wg == 3 ? OFF_PT : OFF_UT), tj * 80 + (wg == 3 ? 0 : 64), ti * 128);
                bulk_commit(); TSTAMP(16 - wg);
                bulk_wait_read(); if (wg == 3) TSTAMP(29);
            }
        }
    }
}

typedef CUresult (*EncodeFn)(CUtensorMap*, CUtensorMapDataType, cuuint32_t, void*, const cuuint64_t*, const cuuint64_t*, const cuuint32_t*, const cuuint32_t*,
                             CUtensorMapInterleave, CUtensorMapSwizzle, CUtensorMapL2promotion, CUtensorMapFloatOOBfill);

void make_map(EncodeFn enc, CUtensorMap* m, const void* p, int rank, const cuuint64_t* dims, const cuuint64_t* strides, const cuuint32_t* box, CUtensorMapSwizzle sw) {
    const cuuint32_t es[5] = {1, 1, 1, 1, 1};
    enc(m, CU_TENSOR_MAP_DATA_TYPE_BFLOAT16, rank, const_cast<void*>(p), dims, strides, box, es, CU_TENSOR_MAP_INTERLEAVE_NONE, sw,
        CU_TENSOR_MAP_L2_PROMOTION_NONE, CU_TENSOR_MAP_FLOAT_OOB_FILL_NONE);
}

}

extern "C" void kernel_launch(void* const* d_in, const int* in_sizes, int n_in, void* d_out, int out_size) {
    (void)in_sizes; (void)n_in; (void)out_size;
    static EncodeFn enc = nullptr;
    static int nsm = 0;
    static void* p_uT = nullptr;
    if (!enc) {
        void* fn = nullptr; cudaDriverEntryPointQueryResult qr;
        cudaGetDriverEntryPoint("cuTensorMapEncodeTiled", &fn, cudaEnableDefault, &qr);
        enc = (EncodeFn)fn;
        cudaGetSymbolAddress(&p_uT, g_uT);
        int dev = 0; cudaGetDevice(&dev);
        cudaDeviceGetAttribute(&nsm, cudaDevAttrMultiProcessorCount, dev);
        cudaFuncSetAttribute(fused_kernel<true>, cudaFuncAttributeMaxDynamicSharedMemorySize, SMEM_TOTAL);
        cudaFuncSetAttribute(fused_kernel<false>, cudaFuncAttributeMaxDynamicSharedMemorySize, SMEM_TOTAL);
    }
    Params P;
    P.u = (const __nv_bfloat16*)d_in[0]; P.logA = (const __nv_bfloat16*)d_in[1]; P.Aim = (const __nv_bfloat16*)d_in[2];
    P.Cre = (const __nv_bfloat16*)d_in[3]; P.Cim = (const __nv_bfloat16*)d_in[4]; P.logdt = (const __nv_bfloat16*)d_in[5];
    P.dskip = (const __nv_bfloat16*)d_in[6]; P.wo = (const __nv_bfloat16*)d_in[9]; P.x = (const __nv_bfloat16*)d_in[7]; P.wqkv = (const __nv_bfloat16*)d_in[8]; P.out = (__nv_bfloat16*)d_out;
    { const cuuint64_t d[2] = {640, 2048}, s[1] = {1280}; const cuuint32_t b[2] = {64, 128}; make_map(enc, &P.mx, d_in[7], 2, d, s, b, CU_TENSOR_MAP_SWIZZLE_128B); }
    { const cuuint64_t d[3] = {640, 640, 3}, s[2] = {3840, 1280}; const cuuint32_t b[3] = {64, 32, 3}; make_map(enc, &P.mw64, d_in[8], 3, d, s, b, CU_TENSOR_MAP_SWIZZLE_128B); }
    { const cuuint64_t d[3] = {640, 640, 3}, s[2] = {3840, 1280}; const cuuint32_t b[3] = {16, 32, 3}; make_map(enc, &P.mw16, d_in[8], 3, d, s, b, CU_TENSOR_MAP_SWIZZLE_32B); }
    { const cuuint64_t d[2] = {1280, 2048}, s[1] = {2560}; const cuuint32_t b[2] = {80, 16}; make_map(enc, &P.mout, d_out, 2, d, s, b, CU_TENSOR_MAP_SWIZZLE_NONE); }
    { const cuuint64_t d[3] = {640, 160, 4}, s[2] = {1280, 204800}; const cuuint32_t b[3] = {32, 160, 2}, c[3] = {16, 160, 2};
      make_map(enc, &P.mwo, d_in[9], 3, d, s, b, CU_TENSOR_MAP_SWIZZLE_64B); make_map(enc, &P.mwo16, d_in[9], 3, d, s, c, CU_TENSOR_MAP_SWIZZLE_64B); }
    { const cuuint64_t d[2] = {1280, 2048}, s[1] = {2560}; const cuuint32_t b[2] = {64, 128}; make_map(enc, &P.mout64, d_out, 2, d, s, b, CU_TENSOR_MAP_SWIZZLE_128B); }
    { const cuuint64_t d[5] = {1024, 2, 80, 2, 4}, s[4] = {4096, 32768, 2048, 8192}; const cuuint32_t b[5] = {64, 2, 10, 2, 1}; make_map(enc, &P.mut, p_uT, 5, d, s, b, CU_TENSOR_MAP_SWIZZLE_128B); }
    { const cuuint64_t d[5] = {64, 16, 2, 16, 40}, s[4] = {128, 2048, 4096, 65536}; const cuuint32_t b[5] = {64, 17, 2, 1, 5}; make_map(enc, &P.mug, p_uT, 5, d, s, b, CU_TENSOR_MAP_SWIZZLE_NONE); }
    { const cuuint64_t d[2] = {1280, 2048}, s[1] = {2560}; const cuuint32_t b[2] = {16, 128}; make_map(enc, &P.mout16, d_out, 2, d, s, b, CU_TENSOR_MAP_SWIZZLE_NONE); }
    cudaLaunchConfig_t cfg = {};
    cfg.gridDim = dim3(nsm == 132 ? 132 : 128); cfg.blockDim = dim3(512); cfg.dynamicSmemBytes = SMEM_TOTAL; cfg.stream = cudaStreamPerThread;
    cudaLaunchAttribute at[1];
    at[0].id = cudaLaunchAttributeClusterDimension; at[0].val.clusterDim.x = 2; at[0].val.clusterDim.y = 1; at[0].val.clusterDim.z = 1;
    cfg.attrs = at; cfg.numAttrs = 1;
    if (nsm == 132) cudaLaunchKernelEx(&cfg, fused_kernel<true>, P);
    else cudaLaunchKernelEx(&cfg, fused_kernel<false>, P);
}
```
